```python
import torch

def _softmax(x, axis=-1):
    return torch.softmax(x, dim=axis)

def _gelu(x):
    return torch.nn.functional.gelu(x, approximate='tanh')

def _silu(x):
    return torch.nn.functional.silu(x)

def _sigmoid(x):
    return torch.sigmoid(x)

def _layernorm(x, axis=-1, eps=1e-05):
    m = x.mean(dim=axis, keepdim=True)
    v = x.var(dim=axis, keepdim=True, unbiased=False)
    return (x - m) / torch.sqrt(v + eps)

def _scatter_add(tgt, idx, src, axis=0):
    return tgt.clone().index_add_(axis, idx, src)

def _segment_sum(src, seg, n):
    out = torch.zeros((n,) + src.shape[1:], dtype=src.dtype)
    return out.index_add_(0, seg, src)

def _pad(x, pw):
    flat = tuple((v for pair in reversed(pw) for v in pair))
    return torch.nn.functional.pad(x, flat)
kernel_name = 'standalone__factorization_afm__recsys'

def setup_inputs():

    _w = lambda a: (lambda t: t.to(torch.bfloat16) if t.is_floating_point() else t)(torch.as_tensor(a))
    B, F, D, V = (1024, 26, 128, min(1000000, 100000))
    A = D
    ii, jj = tuple(torch.triu_indices(F, F, 1).unbind(0))
    return {'idx': _w((lambda lo, hi, *s: torch.randint(lo, hi, s))(0, V, B, F).to(torch.int64)), 'table': _w((lambda *s: torch.randn(*s, dtype=torch.bfloat16) * 0.8)(V, D)), 'ii': _w(ii.to(torch.int64)), 'jj': _w(jj.to(torch.int64)), 'W': _w((lambda *s: torch.randn(*s, dtype=torch.bfloat16) * 0.4)(D, A) * (1.0 / D ** 0.5)), 'b': _w((lambda *s: torch.randn(*s, dtype=torch.bfloat16) * 0.4)(A)), 'h': _w((lambda *s: torch.randn(*s, dtype=torch.bfloat16) * 0.4)(A)), 'p': _w((lambda *s: torch.randn(*s, dtype=torch.bfloat16) * 0.8)(D))}

def reference(idx, table, ii, jj, W, b, h, p):
    emb = table[idx]
    ei = emb[:, ii, :].clone()
    ej = emb[:, jj, :].clone()
    pair = ei * ej
    hid = pair @ W + b
    hid = 0.5 * (hid + torch.abs(hid))
    e = hid @ h
    alpha = _softmax(e, axis=-1)
    pooled = torch.einsum('bp,bpd->bd', alpha, pair)
    return pooled @ p
```

```cpp
#include <cuda_runtime.h>
#include <cuda_bf16.h>
#include <stdint.h>

#define AFM_PHASE 0x35543344u
#define AFM_D1 650
#define AFM_EXTRA 0
#define AFM_EVM 0x9baa1u
#define AFM_GATE 1
#define AFM_ARRA 2
#define AFM_ARRB 2
#define AFM_ZLATE 0
#define AFM_WAITK 0
#define AFM_DA 0
#define AFM_DW 0
#define AFM_WARM 0
#define AFM_DG 0
#define AFM_DT 0
#define AFM_PAD 0

namespace {

constexpr int kB = 1024, kF = 26, kP = 325, kD = 128, kNS = 8;
constexpr int kAssist = 4;
constexpr int kLeftTiles = 3 * kB / kAssist / 64;
constexpr int kRowPitch = 320;
constexpr int kSamplePitch = kF * kRowPitch;
constexpr int kSBO = 2048 + 16;
constexpr int kTPitch = 1408;
constexpr int OFF_B = 0;
constexpr int OFF_E = 35200;
constexpr int OFF_T = OFF_E + kNS * kSamplePitch;
constexpr int kLeftPitch = 5 * 256 + 64;
constexpr int OFF_LT = OFF_E + 64 * kLeftPitch;
constexpr int OFF_LI = OFF_LT + 2 * kLeftTiles * kTPitch;
constexpr int OFF_CB = OFF_LI + kB / kAssist * 5 * 4;
static_assert(OFF_CB >= OFF_T + 40 * kTPitch, "");
constexpr int OFF_SL = OFF_CB + 512;
constexpr int OFF_FS = OFF_SL + 256;
constexpr int OFF_RO = OFF_FS + 32;
constexpr int OFF_OK = OFF_RO + kNS * 128;
constexpr int kSmemBytes = OFF_OK + 32;

__device__ const uint2 kSched[32] = {
  {0x46145f32u,0x00694178u}, {0x41057873u,0x00283c37u}, {0x50557d0au,0x000f3c2du}, {0x73780a7du,0x0000233cu},
  {0x73326e37u,0x00051e5au}, {0x78737d46u,0x00324b5au}, {0x7d3c7869u,0x00641e05u}, {0x64235f50u,0x002d1e0au},
  {0x5a695f0fu,0x003c2332u}, {0x4b6e000au,0x0069322du}, {0x7d375528u,0x006e5a14u}, {0x000a3273u,0x00375f0fu},
  {0x5f283741u,0x00507d55u}, {0x50190a41u,0x00056455u}, {0x5078730fu,0x005a6e5fu}, {0x1969000au,0x005a416eu},
  {0x28784619u,0x000f5f05u}, {0x737d2300u,0x00465014u}, {0x370f7332u,0x0064415au}, {0x1e286e37u,0x002d465au},
  {0x69780a32u,0x00195046u}, {0x0a0f7d19u,0x0014732du}, {0x7d55464bu,0x002d0a78u}, {0x146e0564u,0x00004b19u},
  {0x7864553cu,0x00144605u}, {0x55371e3cu,0x004b1950u}, {0x7d557337u,0x00786905u}, {0x1e287337u,0x00551432u},
  {0x324b1e00u,0x000f2869u}, {0x2d4b5523u,0x0000411eu}, {0x64193c23u,0x006e280au}, {0x37145564u,0x005f234bu},
};
constexpr uint64_t kLeftRows = 0x0907190105ull;
__device__ unsigned long long gLeft[kB * 8];
constexpr uint32_t kLeftTag = 0x7fc5a5a5u;

template <bool kAccumulate>
__device__ __forceinline__ void wgmma_n136(float (&d)[68], uint32_t a0, uint32_t a1, uint32_t a2, uint32_t a3,
                                           uint64_t desc) {
  if (kAccumulate) {
    asm volatile("wgmma.mma_async.sync.aligned.m64n136k16.f32.bf16.bf16 "
      "{%0, %1, %2, %3, %4, %5, %6, %7, %8, %9, %10, %11, %12, %13, %14, %15, %16, %17, %18, %19, %20, %21, %22, %23, %24, %25, %26, %27, %28, %29, %30, %31, %32, %33, %34, %35, %36, %37, %38, %39, %40, %41, %42, %43, %44, %45, %46, %47, %48, %49, %50, %51, %52, %53, %54, %55, %56, %57, %58, %59, %60, %61, %62, %63, %64, %65, %66, %67}, "
      "{%68, %69, %70, %71}, %72, 1, 1, 1, 0;"
      : "+f"(d[0]), "+f"(d[1]), "+f"(d[2]), "+f"(d[3]), "+f"(d[4]), "+f"(d[5]), "+f"(d[6]), "+f"(d[7]), "+f"(d[8]), "+f"(d[9]), "+f"(d[10]), "+f"(d[11]), "+f"(d[12]), "+f"(d[13]), "+f"(d[14]), "+f"(d[15]), "+f"(d[16]), "+f"(d[17]), "+f"(d[18]), "+f"(d[19]), "+f"(d[20]), "+f"(d[21]), "+f"(d[22]), "+f"(d[23]), "+f"(d[24]), "+f"(d[25]), "+f"(d[26]), "+f"(d[27]), "+f"(d[28]), "+f"(d[29]), "+f"(d[30]), "+f"(d[31]), "+f"(d[32]), "+f"(d[33]), "+f"(d[34]), "+f"(d[35]), "+f"(d[36]), "+f"(d[37]), "+f"(d[38]), "+f"(d[39]), "+f"(d[40]), "+f"(d[41]), "+f"(d[42]), "+f"(d[43]), "+f"(d[44]), "+f"(d[45]), "+f"(d[46]), "+f"(d[47]), "+f"(d[48]), "+f"(d[49]), "+f"(d[50]), "+f"(d[51]), "+f"(d[52]), "+f"(d[53]), "+f"(d[54]), "+f"(d[55]), "+f"(d[56]), "+f"(d[57]), "+f"(d[58]), "+f"(d[59]), "+f"(d[60]), "+f"(d[61]), "+f"(d[62]), "+f"(d[63]), "+f"(d[64]), "+f"(d[65]), "+f"(d[66]), "+f"(d[67])
      : "r"(a0), "r"(a1), "r"(a2), "r"(a3), "l"(desc));
  } else {
    asm volatile("wgmma.mma_async.sync.aligned.m64n136k16.f32.bf16.bf16 "
      "{%0, %1, %2, %3, %4, %5, %6, %7, %8, %9, %10, %11, %12, %13, %14, %15, %16, %17, %18, %19, %20, %21, %22, %23, %24, %25, %26, %27, %28, %29, %30, %31, %32, %33, %34, %35, %36, %37, %38, %39, %40, %41, %42, %43, %44, %45, %46, %47, %48, %49, %50, %51, %52, %53, %54, %55, %56, %57, %58, %59, %60, %61, %62, %63, %64, %65, %66, %67}, "
      "{%68, %69, %70, %71}, %72, 0, 1, 1, 0;"
      : "=f"(d[0]), "=f"(d[1]), "=f"(d[2]), "=f"(d[3]), "=f"(d[4]), "=f"(d[5]), "=f"(d[6]), "=f"(d[7]), "=f"(d[8]), "=f"(d[9]), "=f"(d[10]), "=f"(d[11]), "=f"(d[12]), "=f"(d[13]), "=f"(d[14]), "=f"(d[15]), "=f"(d[16]), "=f"(d[17]), "=f"(d[18]), "=f"(d[19]), "=f"(d[20]), "=f"(d[21]), "=f"(d[22]), "=f"(d[23]), "=f"(d[24]), "=f"(d[25]), "=f"(d[26]), "=f"(d[27]), "=f"(d[28]), "=f"(d[29]), "=f"(d[30]), "=f"(d[31]), "=f"(d[32]), "=f"(d[33]), "=f"(d[34]), "=f"(d[35]), "=f"(d[36]), "=f"(d[37]), "=f"(d[38]), "=f"(d[39]), "=f"(d[40]), "=f"(d[41]), "=f"(d[42]), "=f"(d[43]), "=f"(d[44]), "=f"(d[45]), "=f"(d[46]), "=f"(d[47]), "=f"(d[48]), "=f"(d[49]), "=f"(d[50]), "=f"(d[51]), "=f"(d[52]), "=f"(d[53]), "=f"(d[54]), "=f"(d[55]), "=f"(d[56]), "=f"(d[57]), "=f"(d[58]), "=f"(d[59]), "=f"(d[60]), "=f"(d[61]), "=f"(d[62]), "=f"(d[63]), "=f"(d[64]), "=f"(d[65]), "=f"(d[66]), "=f"(d[67])
      : "r"(a0), "r"(a1), "r"(a2), "r"(a3), "l"(desc));
  }
}

__device__ __forceinline__ uint32_t hmul2(uint32_t a, uint32_t b) {
  uint32_t r; asm volatile("mul.rn.bf16x2 %0,%1,%2;" : "=r"(r) : "r"(a), "r"(b)); return r;
}
__device__ __forceinline__ void lds128(uint32_t* r, uint32_t addr) {
  asm volatile("ld.volatile.shared.v4.b32 {%0,%1,%2,%3},[%4];"
               : "=r"(r[0]), "=r"(r[1]), "=r"(r[2]), "=r"(r[3]) : "r"(addr));
}
__device__ __forceinline__ void lds128_if(uint32_t* r, uint32_t addr, int pr) {
  asm volatile("{.reg .pred p; setp.ne.b32 p, %5, 0; @p ld.volatile.shared.v4.b32 {%0,%1,%2,%3},[%4];}"
               : "+r"(r[0]), "+r"(r[1]), "+r"(r[2]), "+r"(r[3]) : "r"(addr), "r"(pr));
}
__device__ __forceinline__ void chain_add(float& d, float a, float m, int one) {
  asm volatile("{.reg .pred p; setp.ne.b32 p, %3, 0; @p add.f32 %0, %1, %2;}" : "+f"(d) : "f"(a), "f"(m), "r"(one));
}
__device__ __forceinline__ void chain_fma(float& d, float a, float r, float m, int one) {
  asm volatile("{.reg .pred p; setp.ne.b32 p, %4, 0; @p fma.rn.f32 %0, %1, %2, %3;}"
               : "+f"(d) : "f"(a), "f"(r), "f"(m), "r"(one));
}
__device__ __forceinline__ float vmax(float a, float c) {
  float r; asm volatile("max.f32 %0, %1, %2;" : "=f"(r) : "f"(a), "f"(c)); return r;
}
__device__ __forceinline__ uint64_t gaddr(const void* base, uint32_t off) {
  uint64_t a;
  asm("{.reg .b32 lo, hi; add.cc.u32 lo, %1, %3; addc.u32 hi, %2, 0; mov.b64 %0, {lo, hi};}"
      : "=l"(a) : "r"((uint32_t)(uint64_t)base), "r"((uint32_t)((uint64_t)base >> 32)), "r"(off));
  return a;
}
__device__ __forceinline__ uint4 ldg128(uint64_t p) {
  uint4 v; asm volatile("ld.global.nc.v4.b32 {%0,%1,%2,%3}, [%4];" : "=r"(v.x), "=r"(v.y), "=r"(v.z), "=r"(v.w) : "l"(p));
  return v;
}
__device__ __forceinline__ uint2 ldg64(uint64_t p) {
  uint2 v; asm volatile("ld.global.nc.v2.b32 {%0,%1}, [%2];" : "=r"(v.x), "=r"(v.y) : "l"(p)); return v;
}
__device__ __forceinline__ int ldg32(uint64_t p) {
  int v; asm volatile("ld.global.nc.b32 %0, [%1];" : "=r"(v) : "l"(p)); return v;
}
__device__ __forceinline__ int row_offset(int r, int V) { return __viaddmin_u32(r, V, r) << 8; }
__device__ __forceinline__ void spin(uint32_t cycles) {
  uint32_t c0, c1;
  asm volatile("mov.u32 %0, %clock;" : "=r"(c0) :: "memory");
  do asm volatile("mov.u32 %0, %clock;" : "=r"(c1) :: "memory"); while (c1 - c0 < cycles);
}
__device__ __forceinline__ float bf2f(uint32_t u16) { return __uint_as_float(u16 << 16); }
__device__ __forceinline__ float ex2(float x) { float r; asm("ex2.approx.ftz.f32 %0, %1;" : "=f"(r) : "f"(x)); return r; }
__device__ __forceinline__ float warp_max(float m) {
  int i = __float_as_int(m);
  i ^= (i >> 31) & 0x7fffffff;
  i = __reduce_max_sync(~0u, i);
  i ^= (i >> 31) & 0x7fffffff;
  return __int_as_float(i);
}
template <int kId> __device__ __forceinline__ void bar_sync() { asm volatile("bar.sync %0, 256;" :: "n"(kId) : "memory"); }
template <int kId> __device__ __forceinline__ void bar_arrive() { asm volatile("bar.arrive %0, 256;" :: "n"(kId) : "memory"); }
__device__ __forceinline__ void bar_sync(int id) { asm volatile("bar.sync %0, 256;" :: "r"(id) : "memory"); }
__device__ __forceinline__ void bar_arrive(int id) { asm volatile("bar.arrive %0, 256;" :: "r"(id) : "memory"); }
__device__ __forceinline__ void wg_fence() { asm volatile("wgmma.fence.sync.aligned;" ::: "memory"); }
__device__ __forceinline__ void wg_commit() { asm volatile("wgmma.commit_group.sync.aligned;" ::: "memory"); }

#define TL(i)
#define TLB(i)
#define TLG(i)
#define TLDUMP()

__device__ __noinline__ float generic_sample(const __nv_bfloat16* E, const int* ii, const int* jj,
                                                const __nv_bfloat16* W, const __nv_bfloat16* bias,
                                                const __nv_bfloat16* h, const __nv_bfloat16* pv, int lane) {
  float m = -INFINITY, den = 0.f, num = 0.f;
  #pragma unroll 1
  for (int p = 0; p < kP; p++) {
    int i = ii[p], j = jj[p];
    if (i < 0) i += kF;
    if (j < 0) j += kF;
    i = min(max(i, 0), kF - 1); j = min(max(j, 0), kF - 1);
    float x[4] = {0.f, 0.f, 0.f, 0.f}, s = 0.f;
    #pragma unroll 1
    for (int d = 0; d < kD; d++) {
      const float pr = __bfloat162float(__hmul(E[i * (kRowPitch / 2) + d], E[j * (kRowPitch / 2) + d]));
      s = fmaf(pr, __bfloat162float(pv[d]), s);
      #pragma unroll
      for (int k = 0; k < 4; k++) x[k] = fmaf(pr, __bfloat162float(W[d * kD + lane + 32 * k]), x[k]);
    }
    float e = 0.f;
    #pragma unroll
    for (int k = 0; k < 4; k++)
      e = fmaf(fmaxf(x[k] + __bfloat162float(bias[lane + 32 * k]), 0.f), __bfloat162float(h[lane + 32 * k]), e);
    #pragma unroll
    for (int o = 16; o; o >>= 1) e += __shfl_xor_sync(~0u, e, o);
    const float mn = fmaxf(m, e), f = __expf(m - mn), w = __expf(e - mn);
    den = den * f + w; num = num * f + w * s; m = mn;
  }
  return num / den;
}

constexpr int BAR_CONS = 0;
constexpr int BAR_READY = 1;
constexpr int BAR_EVENT = 3;
constexpr int BAR_LAST = 5;
constexpr int BAR_TURN = 7;
constexpr int BAR_HELP = 10;
constexpr int BAR_ROWS = 11;
constexpr uint32_t kSmemBase = 1024;
constexpr uint32_t kPhase = AFM_PHASE;
static_assert((kPhase & 0xf000f) == 0x40004, "position of the duplicate pair (z step 0) in the softmax steps");

__global__ void __launch_bounds__(384, 1)
afm_kernel(const int* idx_cta, const __nv_bfloat16* __restrict__ W, const __nv_bfloat16* __restrict__ bias,
           const __nv_bfloat16* __restrict__ h, const __nv_bfloat16* __restrict__ pv, const uint2* __restrict__ sched,
           const __nv_bfloat16* __restrict__ table, const int* __restrict__ ii, const int* __restrict__ jj,
           __nv_bfloat16* __restrict__ out, unsigned long long* left, const int* __restrict__ idx, int V
           ) {
  extern __shared__ __align__(128) uint8_t sm[];
  const int tid = threadIdx.x < 128 ? threadIdx.x + 256 : threadIdx.x - 128;
  const int lane = threadIdx.x & 31, t128 = threadIdx.x & 127;
  const uint32_t sb = (uint32_t)__cvta_generic_to_shared(sm);
  const int helper = threadIdx.x < 128;
  const uint32_t ioff = blockIdx.x * (kNS * kF) + (t128 >> 4);
  const uint64_t ip = gaddr(idx_cta, ioff * 4);
  int r[8][4];
  if (helper && ioff >= kAssist * kNS * kF) {
    #pragma unroll
    for (int m = 0; m < 4; m++) r[0][m] = ldg32(ip + 8 * m * 4);
  }
  uint32_t pinreg = lane;
  auto pin0 = [&]() {
    asm volatile("{.reg .pred p; setp.gt.u32 p, %1, 999; @p mov.u32 %0, %clock;}" : "+r"(pinreg) : "r"(tid) : "memory");
  };
  pin0();
  const int cg = lane & 15, kc = tid >> 4, hsh = (lane >> 4) * 16;
  uint64_t hp = gaddr(h, 16 * cg), bp = gaddr(bias, 16 * cg + 4 * ((tid >> 5) & 3)), pp = gaddr(pv, 8 * lane);
  uint64_t sp = gaddr(sched, 8 * lane), wp = gaddr(W, (32 * (kc >> 2) + 2 * (kc & 3)) * 256 + 16 * cg);
  asm volatile("" : "+l"(hp), "+l"(bp), "+l"(pp), "+l"(sp), "+l"(wp));
  pin0();
  uint4 hv, wv[8];
  uint2 pw, sch;
  uint32_t bw;
  if (!helper) { hv = ldg128(hp); bw = ldg32(bp); pw = ldg64(pp); sch = ldg64(sp); }
  pin0();
  if (!helper) {
    #pragma unroll
    for (int i = 0; i < 8; i++) wv[i] = ldg128(wp + (8 * (i >> 1) + (i & 1)) * 256);
  }
  pin0();
  const int pq = min(tid + 256, kP - 1);
  int rid, iv[2], jv[2];
  {
    uint64_t a0 = gaddr(idx_cta, (max((int)blockIdx.x, kAssist) * (kNS * kF) + (tid >> 5) * kF + min(lane, kF - 1)) * 4);
    uint64_t a1 = gaddr(ii, 4 * tid), a2 = gaddr(ii, 4 * pq), a3 = gaddr(jj, 4 * tid), a4 = gaddr(jj, 4 * pq);
    asm volatile("" : "+l"(a0), "+l"(a1), "+l"(a2), "+l"(a3), "+l"(a4));
    pin0();
    if (!helper) { rid = ldg32(a0); iv[0] = ldg32(a1); iv[1] = ldg32(a2); jv[0] = ldg32(a3); jv[1] = ldg32(a4); }
  }
  pin0();
  const bool tail = t128 < 32;
  uint32_t gdst = kSmemBase + OFF_E + (t128 >> 4) * kRowPitch + (t128 & 15) * 16;
  uint64_t gsrc = gaddr(table, (t128 & 15) * 16);
  asm volatile("" : "+r"(gdst), "+l"(gsrc));
  pin0();
  const int warp = __shfl_sync(~0u, tid >> 5, 0), wg = warp >> 2;
  const uint32_t hs[4] = {hv.x >> hsh, hv.y >> hsh, hv.z >> hsh, hv.w >> hsh};
  uint32_t neg[4];
  #pragma unroll
  for (int k = 0; k < 4; k++) neg[k] = __ballot_sync(~0u, hs[k] & 0x8000u);
  sch.x = __shfl_sync(~0u, sch.x, t128 >> 2);
  sch.y = __shfl_sync(~0u, sch.y, t128 >> 2);
  asm volatile("st.shared.b32 [%0], %1; st.shared.b32 [%0+128], %2;"
               :: "r"(sb + (helper ? OFF_LT : OFF_B + 16 * kSBO) + (tid >> 5) * 16 + (4 * (lane >> 3) + 2 * (lane & 1)) * 128 +
                      ((lane >> 1) & 3) * 4),
                  "r"(tid & 32 ? 0u : pw.x), "r"(tid & 32 ? 0u : pw.y) : "memory");
  uint32_t bq;
  asm volatile("shr.u32 %0, %1, %2;" : "=r"(bq) : "r"(bw), "r"(hsh));

  if (wg == 2) {
    asm volatile("setmaxnreg.dec.sync.aligned.u32 72;");
    uint32_t t0;
    float4 f01 = {}, f23 = {};
    auto lds4 = [](uint32_t a) {
      float4 v; asm volatile("ld.shared.v4.f32 {%0,%1,%2,%3}, [%4];" : "=f"(v.x), "=f"(v.y), "=f"(v.z), "=f"(v.w) : "r"(a) : "memory"); return v;
    };
    auto lds2 = [](uint32_t a) {
      float2 v; asm volatile("ld.shared.v2.f32 {%0,%1}, [%2];" : "=f"(v.x), "=f"(v.y) : "r"(a) : "memory"); return v;
    };
    auto logits = [&](uint32_t q, float mask, float& e0, float& e1) {
      const float4 a = lds4(q), b = lds4(q + 576);
      e0 = fmaf(b.z, f23.z, fmaf(b.x, f23.x, fmaf(a.x, f01.x, fmaf(a.z, f01.z, mask))));
      e1 = fmaf(b.w, f23.w, fmaf(b.y, f23.y, fmaf(a.y, f01.y, a.w * f01.w)));
    };
    if (__builtin_expect(blockIdx.x < kAssist, 0)) {
      #pragma unroll
      for (int w = 0; w < 2; w++) {
        const uint64_t a = gaddr(idx, (blockIdx.x * (kB / kAssist) + 128 * w + t128) * kF * 4);
        #pragma unroll
        for (int k = 0; k < 5; k++) r[k][w] = ldg32(a + ((kLeftRows >> 8 * k) & 0xff) * 4);
      }
      #pragma unroll
      for (int w = 0; w < 2; w++)
        #pragma unroll
        for (int k = 0; k < 5; k++)
          asm volatile("st.shared.b32 [%0], %1;" :: "r"(sb + OFF_LI + ((4 * w + (t128 >> 5)) * 5 + k) * 128 + (lane & 7) * 16 + (lane >> 3) * 4),
                       "r"(row_offset(r[k][w], V)) : "memory");
      asm volatile("bar.sync %0, 128;" :: "n"(BAR_HELP) : "memory");
      if (AFM_DA) spin(AFM_DA);
      const uint32_t oa = sb + OFF_LI + (t128 >> 4) * 16, dst = sb + OFF_E + (t128 >> 4) * kLeftPitch + (t128 & 15) * 16;
      auto fill = [&](int w, int k, const uint32_t (&o)[4]) {
        #pragma unroll
        for (int m = 0; m < 4; m++)
          asm volatile("cp.async.cg.shared.global [%0], [%1], 16;"
                       :: "r"(dst + (32 * w + 8 * m) * kLeftPitch + k * 256), "l"(gaddr((const void*)gsrc, o[m])) : "memory");
      };
      uint32_t ox[2][4], oy[2][4], oz[2][4];
      #pragma unroll 1
      for (int n = 0; n < 10; n++) {
        const int w = n >= 5;
        lds128(oz[0], oa + (n + 15 * w) * 128);
        fill(w, n - 5 * w, oz[0]);
        if (n == 4) asm volatile("cp.async.commit_group;" ::: "memory");
      }
      asm volatile("cp.async.commit_group;" ::: "memory");
      asm volatile("cp.async.wait_group 1;" ::: "memory");
      bar_arrive<BAR_READY>();
      asm volatile("cp.async.wait_group 0;" ::: "memory");
      bar_arrive<BAR_READY + 1>();
      #pragma unroll 1
      for (int e = -2; e < kLeftTiles; e++) {
        const int g = ((e + 5) * 43) >> 7, z = e + 5 - 3 * g;
        #pragma unroll
        for (int w = 0; w < 2; w++) {
          const uint32_t og = oa + (4 * w + (g & 3)) * 5 * 128;
          lds128(oz[w], og + (2 + z) * 128);
          if (z == 0) { lds128(ox[w], og); lds128(oy[w], og + 128); }
        }
        asm volatile("cp.async.wait_group 1;" ::: "memory");
        if (e == kLeftTiles - 1) { bar_sync<BAR_LAST>(); bar_sync<BAR_LAST + 1>(); }
        else bar_sync<BAR_TURN + 2>();
        if (e == kLeftTiles - 2) bar_arrive<BAR_TURN + 1>();
        #pragma unroll
        for (int w = 0; w < 2; w++) {
          if (g < 4) {
            fill(w, 2 + z, oz[w]);
            if (z == 0) { fill(w, 0, ox[w]); fill(w, 1, oy[w]); }
          }
          asm volatile("cp.async.commit_group;" ::: "memory");
        }
        if (e >= 0 && ((e ^ (warp >> 1)) & 1) == 0) {
          const int w = warp & 1, e3 = (e * 43) >> 7;
          f01 = lds4(sb + OFF_FS); f23 = lds4(sb + OFF_FS + 16);
          const uint32_t q = sb + OFF_LT + (kLeftTiles * w + e) * kTPitch;
          float e0, e1;
          logits(q + lane * 16, 0.f, e0, e1);
          const float2 sv = lds2(q + 1152 + lane * 8);
          const uint64_t a = gaddr(left, ((blockIdx.x * (kB / kAssist) + 128 * w + 32 * e3 + lane) * 8 + 2 * (e - 3 * e3)) * 8);
          asm volatile("{.reg .b64 u, v; mov.b64 u, {%1,%2}; mov.b64 v, {%3,%4};\n"
                       "st.relaxed.gpu.global.b64 [%0], u; st.relaxed.gpu.global.b64 [%0+8], v;}"
                       :: "l"(a), "r"(__float_as_uint(e0) ^ kLeftTag), "r"(__float_as_uint(sv.x)),
                          "r"(__float_as_uint(e1) ^ kLeftTag), "r"(__float_as_uint(sv.y)) : "memory");
        }
      }
      return;
    }
    TL(11);
    auto offsets = [&](int smp) {
      #pragma unroll
      for (int m = 0; m < 4; m++) r[smp][m] = row_offset(r[smp][m], V);
    };
    auto gather = [&](int smp) {
      #pragma unroll
      for (int m = 0; m < 4; m++)
        asm volatile("{.reg .pred p; .reg .b32 lo, hi; .reg .b64 a; setp.ne.b32 p, %4, 0;\n"
                     "add.cc.u32 lo, %1, %3; addc.u32 hi, %2, 0; mov.b64 a, {lo, hi};\n"
                     "@p cp.async.cg.shared.global [%0], [a], 16;}"
                     :: "r"(gdst + smp * kSamplePitch + 8 * m * kRowPitch), "r"((uint32_t)gsrc), "r"((uint32_t)(gsrc >> 32)),
                        "r"(r[smp][m]), "r"((int)(m < 3 || tail)) : "memory");
      asm volatile("cp.async.commit_group;" ::: "memory");
    };
    #pragma unroll
    for (int m = 0; m < 4; m++) r[1][m] = ldg32(ip + (kF + 8 * m) * 4);
    pin0();
    offsets(0);
    if (AFM_DG) { asm volatile("" :: "r"(r[0][0]), "r"(r[0][1]), "r"(r[0][2]), "r"(r[0][3])); pin0(); spin(AFM_DG); }
    gather(0);
    asm volatile("mov.u32 %0, %clock;" : "=r"(t0) :: "memory");
    TL(1);
    offsets(1);
    const int v = warp & 3, cw = v & 1;
    const bool second = v >> 1, hi = lane >= 16;
    const int phase = (kPhase >> (16 * cw + 4 * (lane >> 3))) & 15;
    uint32_t pt[5], ps[5];
    {
      const int tl[5] = {second ? 0 : phase, phase + (second ? 5 : 3), phase + (second ? 8 : 10),
                         second ? (phase > 3 ? 3 : 18) : phase + 13, second ? (phase > 4 ? 4 : 19) : phase + 14};
      #pragma unroll
      for (int k = 0; k < 5; k++) {
        pt[k] = sb + OFF_T + (20 * cw + tl[k]) * kTPitch + lane * 16;
        ps[k] = pt[k] + 1152 - lane * 8;
        asm volatile("{.reg .pred p; setp.gt.u32 p, %2, 999; @p mov.u32 %0, %clock; @p mov.u32 %1, %clock;}"
                     : "+r"(pt[k]), "+r"(ps[k]) : "r"(tid));
      }
    }
    const int smp = (blockIdx.x - kAssist) * kNS + (hi ? (6 + v) & 7 : 2 + v), sl = lane & 15;
    uint64_t lp = gaddr(left, (smp * 8 + (sl & 7)) * 8), op = gaddr(out, smp * 2);
    float mask1 = lane || second ? 0.f : -INFINITY, mask2 = lane || !second ? 0.f : -INFINITY;
    asm volatile("" : "+l"(lp), "+l"(op), "+f"(mask1), "+f"(mask2));
    for (;;) {
      uint32_t t1;
      asm volatile("mov.u32 %0, %clock;" : "=r"(t1) :: "memory");
      if (t1 - t0 >= AFM_D1) break;
    }
    gather(1);
    TL(8);
    asm volatile("cp.async.wait_group 1;" ::: "memory");
    bar_arrive<BAR_READY>();
    TL(2);
    asm volatile("bar.sync %0, 384;" :: "n"(BAR_ROWS) : "memory");
    auto fetch = [&](int k) { lds128(reinterpret_cast<uint32_t*>(r[k]), sb + OFF_RO + k * 128 + (t128 >> 4) * 16); };
    fetch(2); fetch(3);
    TL(9);
    asm volatile("cp.async.wait_group 0;" ::: "memory");
    bar_arrive<BAR_READY + 1>();
    gather(2);
    TL(10);
    gather(3);
    asm volatile("cp.async.wait_group 1;" ::: "memory");
    bar_arrive<BAR_EVENT>();
    fetch(4); fetch(5);
    gather(4); gather(5);
    asm volatile("cp.async.wait_group 2;" ::: "memory");
    bar_sync<BAR_EVENT + 1>();
    fetch(6); fetch(7);
    gather(6); gather(7);
    f01 = lds4(sb + OFF_FS); f23 = lds4(sb + OFF_FS + 16);
    const int ok = __all_sync(~0u, *reinterpret_cast<const volatile int*>(sm + OFF_OK + (lane & 7) * 4));
    asm volatile("cp.async.wait_group 0;" ::: "memory");
    bar_arrive<BAR_EVENT>();
    TL(3); TLG(0); TL(7);

    uint2 lv = {kLeftTag ^ 0xff800000u, 0u};
    auto poll = [&]() {
      asm volatile("{.reg .b64 u; ld.relaxed.gpu.global.b64 u, [%2]; mov.b64 {%0,%1}, u;}" : "=r"(lv.x), "=r"(lv.y) : "l"(lp) : "memory");
    };
    float mA = 0.f, dA = 0.f, nA = 0.f, m = -INFINITY, den = 0.f, num = 0.f;
    #pragma unroll
    for (int n = 0; n < 8; n++) {
      bar_sync<BAR_EVENT + 1>();
      if (n == 7 && sl < 6) poll();
      if (n != 5 || second) {
        const int k = n / 3, off = (n - 3 * k) * kTPitch;
        float e0, e1;
        const float2 sv = lds2(ps[k] + off);
        logits(pt[k] + off, n == 1 || n == 7 ? mask1 : n == 0 || n == 4 ? mask2 : 0.f, e0, e1);
        const float mn = fmaxf(m, fmaxf(e0, e1)), f = ex2(m - mn), x0 = ex2(e0 - mn), x1 = ex2(e1 - mn);
        den = fmaf(den, f, x0 + x1);
        num = fmaf(num, f, fmaf(x0, sv.x, x1 * sv.y));
        m = mn;
      }
      if ((n == 2 && second) || (n == 5 && !second)) { mA = m; dA = den; nA = num; m = -INFINITY; den = num = 0.f; }
      asm volatile("" : "+f"(m), "+f"(den), "+f"(num));
      pin0();
    }
    TL(13);
    if (second) {
      float t;
      t = m; m = mA; mA = t;  t = den; den = dA; dA = t;  t = num; num = nA; nA = t;
    }
    if (sl < 6) {
      int it = 1 << 22;
      while (lv.x == 0 && --it) poll();
      asm volatile("st.relaxed.gpu.global.b64 [%0], %1;" :: "l"(lp), "l"(0ull) : "memory");
    }
    __syncwarp();
    TL(14);
    const int last_me = BAR_LAST + cw + (pinreg >> 5);
    bar_arrive(BAR_LAST + 1 - cw);
    bar_sync<BAR_TURN + 2>();
    bar_arrive<BAR_TURN + 1>();
    TLB(16);
    float g[6], mB;
    {
      logits(pt[2] + 2 * kTPitch, 0.f, g[0], g[1]);
      logits(pt[3], 0.f, g[2], g[3]);
      float2 s2 = lds2(ps[2] + 2 * kTPitch);
      const float2 s3 = lds2(ps[3]);
      if (second) { g[0] = g[1] = -INFINITY; s2.x = s2.y = 0.f; }
      const float el = __uint_as_float(lv.x ^ kLeftTag), sv = __uint_as_float(lv.y);
      const float MA = warp_max(hi ? mA : fmaxf(mA, el));
      mB = fmaxf(fmaxf(fmaxf(g[0], g[1]), fmaxf(g[2], g[3])), hi ? fmaxf(m, el) : m);
      const float fA = ex2(mA - MA), x = ex2(el - (hi ? mB : MA)), xs = x * sv;
      dA = fmaf(dA, fA, hi ? 0.f : x); nA = fmaf(nA, fA, hi ? 0.f : xs);
      const float f = ex2(m - mB), y0 = ex2(g[0] - mB), y1 = ex2(g[1] - mB), y2 = ex2(g[2] - mB), y3 = ex2(g[3] - mB);
      den = fmaf(den, f, hi ? x : 0.f) + ((y0 + y1) + (y2 + y3));
      num = fmaf(num, f, hi ? xs : 0.f) + (fmaf(y0, s2.x, y1 * s2.y) + fmaf(y2, s3.x, y3 * s3.y));
    }
    asm volatile("" : "+f"(mB), "+f"(den), "+f"(num), "+f"(dA), "+f"(nA));
    pin0();
    TL(4);
    bar_sync(last_me);
    const float4 ta = lds4(pt[4]), tb4 = lds4(pt[4] + 576);
    const float2 s4 = lds2(ps[4]);
    TL(5);
    g[4] = fmaf(ta.x, f01.x, ta.z * f01.z) + fmaf(tb4.x, f23.x, tb4.z * f23.z);
    g[5] = fmaf(ta.y, f01.y, ta.w * f01.w) + fmaf(tb4.y, f23.y, tb4.w * f23.w);
    const float MB = warp_max(fmaxf(fmaxf(g[4], mB), g[5]));
    const float y4 = ex2(g[4] - MB), y5 = ex2(g[5] - MB), fB = ex2(mB - MB);
    den = fmaf(den, fB, y4 + y5);
    num = fmaf(num, fB, fmaf(y4, s4.x, y5 * s4.y));
    float dk = (hi ? den : dA) + __shfl_xor_sync(~0u, hi ? dA : den, 16);
    float nk = (hi ? num : nA) + __shfl_xor_sync(~0u, hi ? nA : num, 16);
    #pragma unroll
    for (int o = 8; o; o >>= 1) { dk += __shfl_xor_sync(~0u, dk, o); nk += __shfl_xor_sync(~0u, nk, o); }
    if (AFM_DT) { pin0(); spin(AFM_DT); }
    float rk;
    asm("rcp.approx.ftz.f32 %0, %1;" : "=f"(rk) : "f"(dk));
    if (sl == 0) asm volatile("st.global.b16 [%0], %1;" :: "l"(op), "h"(__bfloat16_as_ushort(__float2bfloat16(nk * rk))) : "memory");
    if (__builtin_expect(!ok, 0)) {
      #pragma unroll 1
      for (int w = 0; w < 2; w++) {
        const int sg = w ? (6 + v) & 7 : 2 + v;
        const float gv = generic_sample(reinterpret_cast<const __nv_bfloat16*>(sm + OFF_E + sg * kSamplePitch),
                                       ii, jj, W, bias, h, pv, lane);
        if (lane == 16 * w) *reinterpret_cast<__nv_bfloat16*>(op + (pinreg >> 5)) = __float2bfloat16(gv);
      }
    }
    TL(6); TLG(1); TLDUMP();
  } else {
    TL(9);
    const int c = lane & 3, quad = t128 >> 2, q = warp & 3;
    const int one = __any_sync(~0u, V != 0);
    auto pin = [&]() {
      asm volatile("{.reg .pred p; setp.eq.b32 p, %1, 0; @p mov.u32 %0, %clock;}" : "+r"(pinreg) : "r"(one) : "memory");
    };

    float rs0, rs1, rs2;
    {
      const int npos = 128 - (__popc(neg[0]) + __popc(neg[1]) + __popc(neg[2]) + __popc(neg[3]));
      const int k16 = (npos + 16) >> 5;
      int rem = npos - 16 * k16;
      const int k10 = ((rem + 4) * 18) >> 8; rem -= 10 * k10;
      const int k5 = min(4, (rem * 205) >> 10);
      const int k1 = rem - 5 * k5;
      const uint32_t hq = q == 0 ? hs[0] : q == 1 ? hs[1] : q == 2 ? hs[2] : hs[3];
      const uint32_t nq = q == 0 ? neg[0] : q == 1 ? neg[1] : q == 2 ? neg[2] : neg[3];
      const int nbefore = (q > 0 ? __popc(neg[0]) : 0) + (q > 1 ? __popc(neg[1]) : 0) + (q > 2 ? __popc(neg[2]) : 0) +
                          __popc(nq & ((1u << lane) - 1u));
      const bool isneg = hq & 0x8000u;
      const int r0 = isneg ? nbefore : 32 * q + lane - nbefore;
      const int r1 = r0 - 16 * (isneg ? 4 - k16 : k16);
      const int r2 = r1 - 10 * (isneg ? 4 - k10 : k10);
      const int r3 = r2 - 5 * (isneg ? 4 - k5 : k5);
      const int t1 = (r1 * 205) >> 11, t2 = (r2 * 205) >> 10;
      auto sel = [](int neg_if, int a, int b) {
        int o; asm("slct.s32.s32 %0, %2, %1, %3;" : "=r"(o) : "r"(a), "r"(b), "r"(neg_if)); return o;
      };
      const int tc = sel(r1, r0 >> 4, sel(r2, t1, sel(r3, t2, r3))), cl = isneg ? 3 - tc : tc;
      const int j10 = r1 - 10 * t1;
      const int j = sel(r1, ((isneg ? -r0 : r0 + 1) - 2 * cl) & 15,
                        sel(r2, isneg ? 9 - j10 : j10, sel(r3, 10 + r2 - 5 * t2, 15)));
      const int e = r1 >= 0;
      asm volatile("st.shared.u16 [%0], %1;" :: "r"(sb + OFF_SL + cg * 16 + q * 4 + (lane >> 4) * 2),
                   "h"((unsigned short)(j * kSBO + (2 * cl + e) * 16)) : "memory");
      const float cbv = -bf2f(bq) * bf2f(hq & 0x7fffu);
      asm volatile("st.shared.f32 [%0], %1;"
                   :: "r"(sb + OFF_CB + (j >> 1) * 64 + cl * 16 + (2 * (j & 1) + (e ^ 1)) * 4), "f"(cbv) : "memory");
      const float sE = c < k16 ? 1.f : -1.f, s10 = c < k10 ? 1.f : -1.f, s5 = c < k5 ? 1.f : -1.f, s1 = c < k1 ? 1.f : -1.f;
      rs0 = sE * s10; rs1 = s10 * s5; rs2 = s5 * s1;
      constexpr float kLog2e = 1.4426950408889634f;
      if (tid < 4)
        asm volatile("st.shared.v2.f32 [%0], {%1,%2};" :: "r"(sb + OFF_FS + c * 8), "f"(s1 * kLog2e), "f"(sE * kLog2e) : "memory");
    }
    TL(1);
    bar_sync<BAR_CONS>();
    const int ubits = __shfl_sync(~0u, (tid >> 5) + (blockIdx.x < kAssist ? 8 : 0), 1);
    const int uwarp = ubits & 7, uwg = uwarp >> 2, assist = ubits >> 3;
    uint32_t sl[4];
    lds128(sl, sb + OFF_SL + cg * 16);
    if (AFM_WARM) {
      float w0 = 0.f, w1 = 0.f, w2 = 0.f, w3 = 0.f;
      wg_fence();
      asm volatile("wgmma.mma_async.sync.aligned.m64n8k16.f32.bf16.bf16 {%0,%1,%2,%3}, %4, %4, 0, 1, 1, 0, 0;"
                   : "+f"(w0), "+f"(w1), "+f"(w2), "+f"(w3) : "l"(uint64_t(((kSmemBase + OFF_T) >> 4) | (8 << 16)) | (uint64_t(16) << 32)));
      wg_commit();
      asm volatile("wgmma.wait_group.sync.aligned 0;" ::: "memory");
      asm volatile("{.reg .pred p; setp.eq.b32 p, %2, 0; @p st.shared.f32 [%0], %1;}" :: "r"(lane * 4), "f"(w0), "r"(one) : "memory");
    }
    pin();
    TL(7);
    {
      const uint32_t ha[4] = {hv.x & 0x7fff7fffu, hv.y & 0x7fff7fffu, hv.z & 0x7fff7fffu, hv.w & 0x7fff7fffu};
      const uint32_t dst = sb + OFF_B + kc * 128;
      #pragma unroll
      for (int r = 0; r < 4; r++) {
        uint32_t w[8];
        #pragma unroll
        for (int i = 0; i < 8; i++) w[i] = hmul2(r == 0 ? wv[i].x : r == 1 ? wv[i].y : r == 2 ? wv[i].z : wv[i].w, ha[r]);
        asm volatile("st.shared.v4.b32 [%0], {%1,%2,%3,%4};" :: "r"(dst + (sl[r] & 0xffffu)),
                     "r"(__byte_perm(w[0], w[1], 0x5410)), "r"(__byte_perm(w[2], w[3], 0x5410)),
                     "r"(__byte_perm(w[4], w[5], 0x5410)), "r"(__byte_perm(w[6], w[7], 0x5410)) : "memory");
        asm volatile("st.shared.v4.b32 [%0], {%1,%2,%3,%4};" :: "r"(dst + (sl[r] >> 16)),
                     "r"(__byte_perm(w[0], w[1], 0x7632)), "r"(__byte_perm(w[2], w[3], 0x7632)),
                     "r"(__byte_perm(w[4], w[5], 0x7632)), "r"(__byte_perm(w[6], w[7], 0x7632)) : "memory");
        if (r < 3) pin();
        if (r == 0) TL(8);
      }
    }
    #pragma unroll
    for (int k = 0; k < 1; k++)
      asm volatile("{.reg .pred p; setp.eq.b32 p, %5, 0; @p st.shared.v4.b32 [%0], {%1,%2,%3,%4};}"
                   :: "r"(sb), "r"(r[k][0]), "r"(r[k][1]), "r"(r[k][2]), "r"(r[k][3]), "r"(one) : "memory");
    pin();
    asm volatile("st.shared.b32 [%0], %1;" :: "r"(sb + OFF_RO + warp * 128 + (lane & 7) * 16 + (lane >> 3) * 4),
                 "r"(row_offset(rid, V)) : "memory");
    {
      int ok = sb == kSmemBase;
      #pragma unroll
      for (int k = 0; k < 2; k++) {
        const int i = iv[k], j = jv[k];
        ok &= (unsigned)i < (unsigned)j && (unsigned)j < (unsigned)kF && i * (2 * kF - 3 - i) + 2 * j - 2 == 2 * (k ? pq : tid);
      }
      ok = __all_sync(~0u, ok);
      asm volatile("st.shared.b32 [%0], %1;" :: "r"(sb + OFF_OK + warp * 4), "r"(ok) : "memory");
    }
    asm volatile("bar.arrive %0, 384;" :: "n"(BAR_ROWS) : "memory");
    TL(2);
    if (AFM_DW) spin(AFM_DW);
    asm volatile("setmaxnreg.inc.sync.aligned.u32 216;");
    auto keep = [&](uint32_t v) {
      asm volatile("{.reg .pred p; setp.eq.b32 p, %1, 0; @p mov.u32 %0, %clock;}" : "+r"(v) : "r"(one)); return v;
    };
    const bool assist_t = blockIdx.x < kAssist;
    if (assist_t) { sch.x = 0x00100c08u; sch.y = 0x00040000u; }
    const uint32_t eb_t = kSmemBase + OFF_E + (tid >> 7) * (assist_t ? 32 * kLeftPitch : kSamplePitch);
    uint32_t eb = kSmemBase + OFF_E + uwg * (assist ? 32 * kLeftPitch : kSamplePitch);
    const uint32_t tout = keep(quad * 16 + (c & 1) * 8 + (c >> 1) * 576), sout = keep(1152 + quad * 8);
    const uint32_t c16 = keep(c * 16 + (assist_t ? quad * kLeftPitch : 0));
    const int turn_me = keep(BAR_TURN + (tid >> 7)), turn_ot = keep(BAR_TURN + 1 - (tid >> 7));
    const int ev_bar = keep(BAR_EVENT + (tid >> 7));
    const uint32_t xa = keep(c16 + ((sch.y >> 8) & 0xffu) * 64), ya = keep(c16 + ((sch.y >> 16) & 0xffu) * 64);
    uint32_t za0 = keep(eb_t + c16 + (sch.x & 0xffu) * 64);
    asm volatile("fence.proxy.async.shared::cta;" ::: "memory");
    if (uwg == 1) bar_arrive<BAR_CONS>(); else bar_sync<BAR_CONS>();
    TL(3);
    float cb[32];
    #pragma unroll
    for (int i = 0; i < 8; i++) {
      uint32_t v[4];
      lds128(v, sb + OFF_CB + i * 64 + c * 16);
      cb[4 * i] = __uint_as_float(v[1]); cb[4 * i + 1] = __uint_as_float(v[0]);
      cb[4 * i + 2] = __uint_as_float(v[3]); cb[4 * i + 3] = __uint_as_float(v[2]);
    }

    float acc[68];
    uint32_t A[32], X[16], Y[16], Z[16];
    float T0, T1, s0, s1;
    auto muls = [&](int k) {
      #pragma unroll
      for (int r = 4 * k; r < 4 * k + 4; r++) { A[2 * r] = hmul2(Z[r], X[r]); A[2 * r + 1] = hmul2(Z[r], Y[r]); }
    };
    auto mma = [&](int k0, int k1, uint32_t zero = 0) {
      #pragma unroll
      for (int ks = k0; ks < k1; ks++) {
        const uint64_t desc = uint64_t((((kSmemBase + OFF_B) >> 4) | ((128 >> 4) << 16)) + ks * 16 + zero) |
                              (uint64_t(kSBO >> 4) << 32);
        if (ks == 0) wgmma_n136<false>(acc, A[0], A[1], A[2], A[3], desc);
        else wgmma_n136<true>(acc, A[4 * ks], A[4 * ks + 1], A[4 * ks + 2], A[4 * ks + 3], desc);
      }
    };
    auto epilogue = [&](int tile) {
      asm volatile("wgmma.wait_group.sync.aligned 0;" ::: "memory");
      #pragma unroll
      for (int i = 0; i < AFM_PAD; i++) pin();
      #pragma unroll
      for (int i = 0; i < 68; i++) asm volatile("" : "+f"(acc[i]) :: "memory");
      float m0[32], m1[32], tmp;
      auto maxes = [&](int u) {
        const int j0 = u & 15, p0 = u >> 4, j1 = 15 - (u & 15), p1 = 1 - (u >> 4);
        m0[u] = vmax(acc[4 * j0 + p0], cb[2 * j0 + p0]);
        m1[u] = vmax(acc[4 * j1 + 2 + p1], cb[2 * j1 + p1]);
      };
      maxes(0); maxes(1);
      T1 = m0[0]; T0 = m1[0];
      #pragma unroll
      for (int u = 1; u < 32; u++) {
        if (u < 31) maxes(u + 1);
        if (u < 16) {
          chain_add(T1, T1, m0[u], one);
          if (u == 1) chain_fma(T0, T0, rs2, m1[u], one);
          else if (u == 6) chain_fma(T0, T0, rs1, m1[u], one);
          else chain_add(T0, T0, m1[u], one);
        } else if (u == 16) {
          tmp = fmaf(T1, rs0, m0[u]);
          chain_fma(T1, T0, rs0, m1[u], one);
        } else {
          if (u == 26) chain_fma(T0, T0, rs1, m0[u], one);
          else if (u == 31) chain_fma(T0, T0, rs2, m0[u], one);
          else chain_add(T0, u == 17 ? tmp : T0, m0[u], one);
          chain_add(T1, T1, m1[u], one);
        }
      }
      asm volatile("add.f32 %0, %2, 0f00000000; add.f32 %1, %3, 0f00000000;" : "=f"(s0), "=f"(s1) : "f"(acc[64]), "f"(acc[66]));
    };

    int bstep = (kPhase >> (4 * uwarp)) & 15;
    if (bstep == 5 || assist) bstep = 0;
    const int estep = bstep - assist, lstep = 4 - 2 * assist;
    int step = 0;
    uint32_t za, tb = kSmemBase + (assist ? OFF_LT + kLeftTiles * uwg * kTPitch : OFF_T + 20 * uwg * kTPitch);

    auto advance = [&]() {
      asm volatile("" : "+r"(step), "+r"(eb));
      step = step == lstep ? 0 : step + 1;
      if (step == estep) eb += eb >= kSmemBase + OFF_E + 6 * kSamplePitch ? -6 * kSamplePitch : 2 * kSamplePitch;
      asm volatile("{.reg .b32 b; prmt.b32 b, %1, %2, %3; shl.b32 b, b, 6; add.u32 %0, b, %4;}"
                   : "=r"(za) : "r"(sch.x), "r"(sch.y), "r"(0x7770 | step), "r"(c16));
    };
    auto loads = [&](int k, int bn, int more) {
      lds128_if(&X[4 * k], eb + xa + k * 64, bn); lds128_if(&Y[4 * k], eb + ya + k * 64, bn);
      lds128_if(&Z[4 * k], eb + za + k * 64, more);
    };
    auto store = [&](uint32_t base) {
      asm volatile("st.volatile.shared.v2.f32 [%0], {%1,%2};" :: "r"(base + tout), "f"(T0), "f"(T1) : "memory");
      asm volatile("st.volatile.shared.v2.f32 [%0], {%1,%2};" :: "r"(base + sout), "f"(s0), "f"(s1) : "memory");
    };

    bar_sync(turn_me - (BAR_TURN - BAR_READY));
    TLB(4);
    #pragma unroll
    for (int k = 0; k < 4; k++) {
      if (k == AFM_GATE && uwg == 1) bar_sync<BAR_TURN + 1>();
      lds128(&X[4 * k], eb + xa + k * 64); lds128(&Y[4 * k], eb + ya + k * 64); lds128(&Z[4 * k], za0 + k * 64);
      if (k + 10 == AFM_ARRA && uwg == 0) bar_arrive<BAR_TURN + 1>();
    }
    if (AFM_GATE == 4 && uwg == 1) bar_sync<BAR_TURN + 1>();
    TL(5);
    #pragma unroll
    for (int k = 0; k < 4; k++) {
      muls(k);
      if (k == 0 && AFM_WAITK)
        asm volatile("{.reg .pred p; setp.eq.b32 p, %2, 0; @p st.shared.b32 [%0], %1;}" :: "r"(za0), "r"(Z[4 * AFM_WAITK]), "r"(one) : "memory");
      wg_fence();
      mma(2 * k, 2 * k + 2);
      if (AFM_ARRA == AFM_ARRB) { if (k == AFM_ARRA) bar_arrive(turn_ot); }
      else {
        if (k == AFM_ARRA && uwg == 0) bar_arrive<BAR_TURN + 1>();
        if (k == AFM_ARRB && uwg == 1) bar_arrive<BAR_TURN>();
      }
      pin();
    }
    wg_commit();
    advance();
    asm volatile("{.reg .pred p; setp.ne.b32 p, %3, 0; @p add.u32 %0, %1, %2;}" : "+r"(za0) : "r"(eb), "r"(za), "r"(one));
    advance();
    asm volatile("{.reg .pred p; setp.ne.b32 p, %1, 0; @p bar.sync %0, 256;}" :: "n"(BAR_TURN + 2), "r"(assist & uwg) : "memory");
    bar_sync(turn_me);
    #pragma unroll
    for (int k = 0; k < 4; k++) lds128(&Z[4 * k], za0 + k * 64);
    asm volatile("{.reg .pred p; setp.ne.b32 p, %1, 0; @p bar.sync %0, 256;}" :: "n"(BAR_TURN + 2), "r"(assist & uwg) : "memory");
    asm volatile("{.reg .pred p; setp.eq.b32 p, %1, 0; @p st.volatile.shared.b32 [%0], %0;}" :: "r"(c16), "r"(one) : "memory");
    uint32_t ev_mask = assist ? 1u << (kLeftTiles - 1) : 0x80021u + uwg * (AFM_EVM - 0x80021u);
    const uint32_t end_lo = 4 * (uwg & assist), end_hi = uwg ? assist << 20 : 3;
    int t = 0, more;
    #pragma unroll 1
    do {
      epilogue(t);
      pin();
      muls(0);
      store(tb);
      #pragma unroll
      for (int k = 1; k < 4; k++)
        asm volatile("{.reg .pred p; setp.eq.b32 p, %2, 0; @p st.shared.b32 [%0], %1;}" :: "r"(za0 + 4 * k), "r"(Z[4 * k]), "r"(one) : "memory");
      more = ev_mask > 3;
      const int bn = step == bstep && more;
      bar_arrive(turn_ot);
      #pragma unroll
      for (int k = 0; k < 3; k++) {
        pin();
        wg_fence();
        mma(2 * k, 2 * k + 2);
        muls(k + 1);
        loads(k, bn, more);
      }
      pin();
      wg_fence();
      mma(6, 7);
      loads(3, bn, more);
      mma(7, 8, ev_mask >> 31);
      wg_commit();
      tb += AFM_EXTRA && !assist && t > 5 && t <= 5 + AFM_EXTRA ? 0 : kTPitch;
      asm volatile("{.reg .pred p; setp.ne.b32 p, %1, 0; @p bar.sync %0, 256;}" :: "r"(ev_bar), "r"(ev_mask & 1) : "memory");
      bar_sync(turn_me);
      asm volatile("{.reg .pred p; setp.le.u32 p, %1, %2; @p bar.sync %0, 256;}" :: "n"(BAR_TURN + 2), "r"(ev_mask - end_lo), "r"(end_hi) : "memory");
      asm volatile("{.reg .pred p; setp.eq.b32 p, %5, 0; @p st.volatile.shared.v4.f32 [%0], {%1,%2,%3,%4};}"
                   :: "r"(c16), "f"(T0), "f"(T1), "f"(s0), "f"(s1), "r"(one) : "memory");
      pin();
      advance();
      ev_mask >>= AFM_EXTRA && !assist && t > 5 && t <= 5 + AFM_EXTRA ? 0 : 1;
      t++;
    } while (more);
    const int last_bar = turn_me - (BAR_TURN - BAR_LAST) + (pinreg >> 5);
    asm volatile("" :: "r"(last_bar));
    epilogue(19);
    store(tb);
    bar_arrive(last_bar);
    TL(6);
    TLDUMP();
  }
}

}

extern "C" void kernel_launch(void* const* d_in, const int* in_sizes, int n_in, void* d_out, int out_size) {
  (void)n_in; (void)out_size;
  void *sched = nullptr, *left = nullptr;
  cudaGetSymbolAddress(&sched, kSched);
  cudaGetSymbolAddress(&left, gLeft);
  cudaFuncSetAttribute(afm_kernel, cudaFuncAttributeMaxDynamicSharedMemorySize, kSmemBytes);
  afm_kernel<<<kB / kNS + kAssist, 384, kSmemBytes>>>(
      (const int*)d_in[0] - kAssist * kNS * kF, (const __nv_bfloat16*)d_in[4], (const __nv_bfloat16*)d_in[5],
      (const __nv_bfloat16*)d_in[6], (const __nv_bfloat16*)d_in[7], (const uint2*)sched,
      (const __nv_bfloat16*)d_in[1], (const int*)d_in[2], (const int*)d_in[3], (__nv_bfloat16*)d_out, (unsigned long long*)left, (const int*)d_in[0],
      in_sizes[1] / kD
      );
}
```

```cpp
#include <cuda_runtime.h>
#include <cuda_bf16.h>
#include <cuda_fp16.h>
#include <stdint.h>

#define AFM_G1 4
#define AFM_WARM 1
#define AFM_X 0
#define AFM_ARR 2
#define AFM_PACE 0
#define AFM_EXTRA 0

namespace {

constexpr int kB = 1024, kF = 26, kP = 325, kD = 128, kNS = 8;
constexpr int kAssist = 4;
constexpr int kRowPitch = 320;
constexpr int kSamplePitch = kF * kRowPitch;
constexpr int kTPitch = 1152;
constexpr uint32_t kSmemBase = 1024;
constexpr uint32_t S_B = kSmemBase;
constexpr uint32_t S_C = S_B + 32768;
constexpr uint32_t S_G = S_C + 1024;
constexpr uint32_t S_I = S_G + 256;
constexpr uint32_t S_RO = S_I + 128;
constexpr uint32_t S_E = S_RO + 1280;
constexpr uint32_t S_T = S_E + kNS * kSamplePitch;
constexpr uint32_t S_END = S_T + 40 * kTPitch;
constexpr int kSmemBytes = S_END - kSmemBase;

__device__ const uint2 kSched[32] = {
  {0x05555028u,0x5050506eu}, {0x5a323705u,0x37373773u}, {0x64551932u,0x1919190au}, {0x4b5a2823u,0x28282819u},
  {0x695a460au,0x4646466eu}, {0x78554b41u,0x4b4b4b69u}, {0x0a144b2du,0x4b4b4b73u}, {0x7d233c0au,0x3c3c3c50u},
  {0x6e143723u,0x37373778u}, {0x73195046u,0x50505078u}, {0x2d5a500fu,0x50505041u}, {0x6e0f4b32u,0x4b4b4b3cu},
  {0x69145032u,0x5050501eu}, {0x642d0523u,0x05050569u}, {0x235f4632u,0x46464641u}, {0x1e5f192du,0x1919196eu},
  {0x2d554637u,0x4646463cu}, {0x5a555f14u,0x5f5f5f7du}, {0x69190f37u,0x0f0f0f7du}, {0x64460f28u,0x0f0f0f14u},
  {0x0514193cu,0x19191941u}, {0x1e410a37u,0x0a0a0a28u}, {0x7832282du,0x2828287du}, {0x5f0f050au,0x05050578u},
  {0x3c5a001eu,0x46002878u}, {0x5523001eu,0x7373730fu}, {0x64500037u,0x005f5a4bu}, {0x735f373cu,0x00782364u},
  {0x6e005541u,0x64697d73u}, {0x695f5028u,0x73323c00u}, {0x46051e4bu,0x0073007du}, {0x7d002d1eu,0x4b6e4164u},
};
__device__ unsigned long long gLeft[kB * 8];
constexpr uint32_t kLeftTag = 0x7fc5a5a5u;

template <bool kAccumulate>
__device__ __forceinline__ void wgmma_n128(uint32_t (&d)[32], const uint32_t* a, uint64_t desc) {
  if (kAccumulate) {
    asm volatile("wgmma.mma_async.sync.aligned.m64n128k16.f16.f16.f16 "
      "{%0, %1, %2, %3, %4, %5, %6, %7, %8, %9, %10, %11, %12, %13, %14, %15, %16, %17, %18, %19, %20, %21, %22, %23, %24, %25, %26, %27, %28, %29, %30, %31}, "
      "{%32, %33, %34, %35}, %36, 1, 1, 1, 1;"
      : "+r"(d[0]), "+r"(d[1]), "+r"(d[2]), "+r"(d[3]), "+r"(d[4]), "+r"(d[5]), "+r"(d[6]), "+r"(d[7]), "+r"(d[8]), "+r"(d[9]), "+r"(d[10]), "+r"(d[11]), "+r"(d[12]), "+r"(d[13]), "+r"(d[14]), "+r"(d[15]), "+r"(d[16]), "+r"(d[17]), "+r"(d[18]), "+r"(d[19]), "+r"(d[20]), "+r"(d[21]), "+r"(d[22]), "+r"(d[23]), "+r"(d[24]), "+r"(d[25]), "+r"(d[26]), "+r"(d[27]), "+r"(d[28]), "+r"(d[29]), "+r"(d[30]), "+r"(d[31])
      : "r"(a[0]), "r"(a[1]), "r"(a[2]), "r"(a[3]), "l"(desc));
  } else {
    asm volatile("wgmma.mma_async.sync.aligned.m64n128k16.f16.f16.f16 "
      "{%0, %1, %2, %3, %4, %5, %6, %7, %8, %9, %10, %11, %12, %13, %14, %15, %16, %17, %18, %19, %20, %21, %22, %23, %24, %25, %26, %27, %28, %29, %30, %31}, "
      "{%32, %33, %34, %35}, %36, 0, 1, 1, 1;"
      : "=r"(d[0]), "=r"(d[1]), "=r"(d[2]), "=r"(d[3]), "=r"(d[4]), "=r"(d[5]), "=r"(d[6]), "=r"(d[7]), "=r"(d[8]), "=r"(d[9]), "=r"(d[10]), "=r"(d[11]), "=r"(d[12]), "=r"(d[13]), "=r"(d[14]), "=r"(d[15]), "=r"(d[16]), "=r"(d[17]), "=r"(d[18]), "=r"(d[19]), "=r"(d[20]), "=r"(d[21]), "=r"(d[22]), "=r"(d[23]), "=r"(d[24]), "=r"(d[25]), "=r"(d[26]), "=r"(d[27]), "=r"(d[28]), "=r"(d[29]), "=r"(d[30]), "=r"(d[31])
      : "r"(a[0]), "r"(a[1]), "r"(a[2]), "r"(a[3]), "l"(desc));
  }
}

__device__ __forceinline__ void wgmma_n136(float (&d)[68], const uint32_t* a, uint64_t desc, int accumulate) {
  asm volatile("{.reg .pred p; setp.ne.b32 p, %73, 0; wgmma.mma_async.sync.aligned.m64n136k16.f32.bf16.bf16 "
    "{%0, %1, %2, %3, %4, %5, %6, %7, %8, %9, %10, %11, %12, %13, %14, %15, %16, %17, %18, %19, %20, %21, %22, %23, %24, %25, %26, %27, %28, %29, %30, %31, %32, %33, %34, %35, %36, %37, %38, %39, %40, %41, %42, %43, %44, %45, %46, %47, %48, %49, %50, %51, %52, %53, %54, %55, %56, %57, %58, %59, %60, %61, %62, %63, %64, %65, %66, %67}, "
    "{%68, %69, %70, %71}, %72, p, 1, 1, 1;}"
    : "+f"(d[0]), "+f"(d[1]), "+f"(d[2]), "+f"(d[3]), "+f"(d[4]), "+f"(d[5]), "+f"(d[6]), "+f"(d[7]), "+f"(d[8]), "+f"(d[9]), "+f"(d[10]), "+f"(d[11]), "+f"(d[12]), "+f"(d[13]), "+f"(d[14]), "+f"(d[15]), "+f"(d[16]), "+f"(d[17]), "+f"(d[18]), "+f"(d[19]), "+f"(d[20]), "+f"(d[21]), "+f"(d[22]), "+f"(d[23]), "+f"(d[24]), "+f"(d[25]), "+f"(d[26]), "+f"(d[27]), "+f"(d[28]), "+f"(d[29]), "+f"(d[30]), "+f"(d[31]), "+f"(d[32]), "+f"(d[33]), "+f"(d[34]), "+f"(d[35]), "+f"(d[36]), "+f"(d[37]), "+f"(d[38]), "+f"(d[39]), "+f"(d[40]), "+f"(d[41]), "+f"(d[42]), "+f"(d[43]), "+f"(d[44]), "+f"(d[45]), "+f"(d[46]), "+f"(d[47]), "+f"(d[48]), "+f"(d[49]), "+f"(d[50]), "+f"(d[51]), "+f"(d[52]), "+f"(d[53]), "+f"(d[54]), "+f"(d[55]), "+f"(d[56]), "+f"(d[57]), "+f"(d[58]), "+f"(d[59]), "+f"(d[60]), "+f"(d[61]), "+f"(d[62]), "+f"(d[63]), "+f"(d[64]), "+f"(d[65]), "+f"(d[66]), "+f"(d[67])
    : "r"(a[0]), "r"(a[1]), "r"(a[2]), "r"(a[3]), "l"(desc), "r"(accumulate));
}
__device__ __forceinline__ void wgmma_n8(float (&d)[4], const uint32_t* a, uint64_t desc, int accumulate) {
  asm volatile("{.reg .pred p; setp.ne.b32 p, %9, 0; wgmma.mma_async.sync.aligned.m64n8k16.f32.bf16.bf16 "
    "{%0, %1, %2, %3}, {%4, %5, %6, %7}, %8, p, 1, 1, 0;}"
    : "+f"(d[0]), "+f"(d[1]), "+f"(d[2]), "+f"(d[3])
    : "r"(a[0]), "r"(a[1]), "r"(a[2]), "r"(a[3]), "l"(desc), "r"(accumulate));
}

__device__ __forceinline__ uint32_t hmul(uint32_t a, uint32_t b) {
  uint32_t r; asm volatile("mul.rn.f16x2 %0,%1,%2;" : "=r"(r) : "r"(a), "r"(b)); return r;
}
__device__ __forceinline__ uint32_t hadd(uint32_t a, uint32_t b) {
  uint32_t r; asm volatile("add.rn.f16x2 %0,%1,%2;" : "=r"(r) : "r"(a), "r"(b)); return r;
}
__device__ __forceinline__ uint32_t hfma(uint32_t a, uint32_t b, uint32_t c) {
  uint32_t r; asm volatile("fma.rn.f16x2 %0,%1,%2,%3;" : "=r"(r) : "r"(a), "r"(b), "r"(c)); return r;
}
__device__ __forceinline__ uint32_t hfma_relu(uint32_t a, uint32_t b, uint32_t c) {
  uint32_t r; asm volatile("fma.rn.relu.f16x2 %0,%1,%2,%3;" : "=r"(r) : "r"(a), "r"(b), "r"(c)); return r;
}
__device__ __forceinline__ uint32_t fold(uint32_t a, uint32_t b) {
  return hadd(__byte_perm(a, b, 0x5410), __byte_perm(a, b, 0x7632));
}
__device__ __forceinline__ float2 h2f(uint32_t v) { return __half22float2(*reinterpret_cast<__half2*>(&v)); }
__device__ __forceinline__ uint32_t bmul(uint32_t a, uint32_t b) {
  uint32_t r; asm("mul.rn.bf16x2 %0,%1,%2;" : "=r"(r) : "r"(a), "r"(b)); return r;
}
__device__ __forceinline__ uint32_t amax(uint32_t a, uint32_t b) {
  uint32_t r; asm("max.NaN.xorsign.abs.bf16x2 %0,%1,%2;" : "=r"(r) : "r"(a), "r"(b)); return r;
}
__device__ __forceinline__ uint32_t amax(const uint4& v) { return amax(amax(v.x, v.y), amax(v.z, v.w)); }
__device__ __forceinline__ uint32_t warp_amax(uint32_t m) { return __reduce_max_sync(~0u, amax(m, m << 16) & 0x7fff0000u); }
__device__ __forceinline__ uint32_t pow2_bf16x2(int field) { return field * 0x00800080u; }
__device__ __forceinline__ uint32_t to_half(uint32_t x, uint32_t f) {
  const uint32_t y = bmul(x, f);
  return y + 7u * (y & 0x0fff0fffu);
}
__device__ __forceinline__ void lds128(uint32_t* r, uint32_t addr) {
  asm volatile("ld.volatile.shared.v4.b32 {%0,%1,%2,%3},[%4];"
               : "=r"(r[0]), "=r"(r[1]), "=r"(r[2]), "=r"(r[3]) : "r"(addr));
}
__device__ __forceinline__ void lds128_if(uint32_t* r, uint32_t addr, int pr) {
  asm volatile("{.reg .pred p; setp.ne.b32 p, %5, 0; @p ld.volatile.shared.v4.b32 {%0,%1,%2,%3},[%4];}"
               : "+r"(r[0]), "+r"(r[1]), "+r"(r[2]), "+r"(r[3]) : "r"(addr), "r"(pr));
}
__device__ __forceinline__ uint32_t lds32(uint32_t addr) {
  uint32_t r; asm volatile("ld.volatile.shared.b32 %0,[%1];" : "=r"(r) : "r"(addr)); return r;
}
__device__ __forceinline__ void sts32(uint32_t addr, uint32_t a) {
  asm volatile("st.volatile.shared.b32 [%0], %1;" :: "r"(addr), "r"(a) : "memory");
}
__device__ __forceinline__ void sts64(uint32_t addr, uint32_t a, uint32_t b) {
  asm volatile("st.volatile.shared.v2.b32 [%0], {%1,%2};" :: "r"(addr), "r"(a), "r"(b) : "memory");
}
__device__ __forceinline__ void sts128(uint32_t addr, uint32_t a, uint32_t b, uint32_t c, uint32_t d) {
  asm volatile("st.volatile.shared.v4.b32 [%0], {%1,%2,%3,%4};" :: "r"(addr), "r"(a), "r"(b), "r"(c), "r"(d) : "memory");
}
__device__ __forceinline__ void sts32_if(uint32_t addr, uint32_t a, int pr) {
  asm volatile("{.reg .pred p; setp.ne.b32 p, %2, 0; @p st.volatile.shared.b32 [%0], %1;}" :: "r"(addr), "r"(a), "r"(pr) : "memory");
}
__device__ __forceinline__ void sts128_if(uint32_t addr, uint32_t a, uint32_t b, uint32_t c, uint32_t d, int pr) {
  asm volatile("{.reg .pred p; setp.ne.b32 p, %5, 0; @p st.volatile.shared.v4.b32 [%0], {%1,%2,%3,%4};}"
               :: "r"(addr), "r"(a), "r"(b), "r"(c), "r"(d), "r"(pr) : "memory");
}
__device__ __forceinline__ uint64_t gaddr(uint64_t base, uint32_t off) {
  uint64_t a;
  asm("{.reg .b32 lo, hi; add.cc.u32 lo, %1, %3; addc.u32 hi, %2, 0; mov.b64 %0, {lo, hi};}"
      : "=l"(a) : "r"((uint32_t)base), "r"((uint32_t)(base >> 32)), "r"(off));
  return a;
}
__device__ __forceinline__ uint64_t gaddr(const void* base, uint32_t off) { return gaddr((uint64_t)base, off); }
__device__ __forceinline__ uint4 ldg128(uint64_t p) {
  uint4 v; asm volatile("ld.global.v4.b32 {%0,%1,%2,%3}, [%4];" : "=r"(v.x), "=r"(v.y), "=r"(v.z), "=r"(v.w) : "l"(p));
  return v;
}
__device__ __forceinline__ uint2 ldg64(uint64_t p) {
  uint2 v; asm volatile("ld.global.v2.b32 {%0,%1}, [%2];" : "=r"(v.x), "=r"(v.y) : "l"(p)); return v;
}
__device__ __forceinline__ int ldg32(uint64_t p) {
  int v; asm volatile("ld.global.b32 %0, [%1];" : "=r"(v) : "l"(p)); return v;
}
__device__ __forceinline__ uint32_t row_offset(int r, int V) { return __viaddmin_u32(r, V, r) << 8; }
__device__ __forceinline__ float ex2(float x) { float r; asm("ex2.approx.ftz.f32 %0, %1;" : "=f"(r) : "f"(x)); return r; }
__device__ __forceinline__ float warp_max(float m) {
  int i = __float_as_int(m);
  i ^= (i >> 31) & 0x7fffffff;
  i = __reduce_max_sync(~0u, i);
  i ^= (i >> 31) & 0x7fffffff;
  return __int_as_float(i);
}
__device__ __forceinline__ void bar_sync(int id, int n) { asm volatile("bar.sync %0, %1;" :: "r"(id), "r"(n) : "memory"); }
__device__ __forceinline__ void bar_arrive(int id, int n) { asm volatile("bar.arrive %0, %1;" :: "r"(id), "r"(n) : "memory"); }
__device__ __forceinline__ void bar_sync_if(int id, int n, int pr) {
  asm volatile("{.reg .pred p; setp.ne.b32 p, %2, 0; @p bar.sync %0, %1;}" :: "r"(id), "r"(n), "r"(pr) : "memory");
}
__device__ __forceinline__ void bar_arrive_if(int id, int n, int pr) {
  asm volatile("{.reg .pred p; setp.ne.b32 p, %2, 0; @p bar.arrive %0, %1;}" :: "r"(id), "r"(n), "r"(pr) : "memory");
}
__device__ __forceinline__ int bar_any(int id, int n, int pr) {
  int r;
  asm volatile("{.reg .pred p, q; setp.ne.b32 p, %3, 0; bar.red.or.pred q, %1, %2, p; selp.b32 %0, 1, 0, q;}"
               : "=r"(r) : "r"(id), "r"(n), "r"(pr) : "memory");
  return __any_sync(~0u, r);
}
__device__ __forceinline__ void wg_fence() { asm volatile("wgmma.fence.sync.aligned;" ::: "memory"); }
__device__ __forceinline__ void wg_commit() { asm volatile("wgmma.commit_group.sync.aligned;" ::: "memory"); }

__device__ __forceinline__ uint32_t tau_of(int field) {
  uint32_t r; asm("cvt.rn.f16x2.f32 %0, %1, %1;" : "=r"(r) : "f"(__int_as_float(max(field, 0) << 23))); return r;
}
struct Scales {
  int ka, kb, ft, fe, fs, bad;
  __device__ __forceinline__ Scales(int eh, int eb, int ep, int eg, int ew)
      : ka(126 + min((131 - eg) >> 1, 5)), kb((eb - 136) >> 1), ft(eb - 2), fe(eh + 5), fs(ep + 3),
        bad((eg > 133) | (eg < 114 && ew) | (ew - eg > 10) | (eb > 145) | (ep > 138) | (eh > 253)) {}
  __device__ __forceinline__ int k(int em) const { return max(em - ka, kb); }
  __device__ __forceinline__ uint32_t tau(int n) const { return tau_of(ft - n); }
  __device__ __forceinline__ float logit(int n) const { return __int_as_float(max(fe + n, 0) << 23) * 1.4426950408889634f; }
  __device__ __forceinline__ float dot(int n) const { return __int_as_float(max(fs + n, 0) << 23); }
};

#define TL(i)
#define TLB(i)
#define TLA(i)
#define TLG(i)
#define TLDUMP()

__device__ __noinline__ float plain_sample(const int* rows, const __nv_bfloat16* table, int V, const int* ii, const int* jj,
                                           const __nv_bfloat16* W, const __nv_bfloat16* bias,
                                           const __nv_bfloat16* h, const __nv_bfloat16* pv, int lane) {
  float m = -INFINITY, den = 0.f, num = 0.f;
  #pragma unroll 1
  for (int p = 0; p < kP; p++) {
    int i = ii[p], j = jj[p];
    if (i < 0) i += kF;
    if (j < 0) j += kF;
    const __nv_bfloat16* ei = table + row_offset(rows[min(max(i, 0), kF - 1)], V) / 2;
    const __nv_bfloat16* ej = table + row_offset(rows[min(max(j, 0), kF - 1)], V) / 2;
    float x[4] = {0.f, 0.f, 0.f, 0.f}, s = 0.f;
    #pragma unroll 4
    for (int d = 0; d < kD; d++) {
      const float pr = __bfloat162float(__hmul(ei[d], ej[d]));
      s = fmaf(pr, __bfloat162float(pv[d]), s);
      #pragma unroll
      for (int k = 0; k < 4; k++) x[k] = fmaf(pr, __bfloat162float(W[d * kD + lane + 32 * k]), x[k]);
    }
    float e = 0.f;
    #pragma unroll
    for (int k = 0; k < 4; k++) {
      const float y = x[k] + __bfloat162float(bias[lane + 32 * k]);
      e = fmaf(0.5f * (y + fabsf(y)), __bfloat162float(h[lane + 32 * k]), e);
    }
    #pragma unroll
    for (int o = 16; o; o >>= 1) e += __shfl_xor_sync(~0u, e, o);
    const float mn = e > m || e != e ? e : m, f = __expf(m - mn), w = __expf(e - mn);
    den = den * f + w; num = num * f + w * s; m = mn;
  }
  return num / den;
}

constexpr int BAR_CONST = 0;
constexpr int BAR_B = 1;
constexpr int BAR_START = 2;
constexpr int BAR_HELP = 4;
constexpr int BAR_AUX = 5;
constexpr int BAR_READY = 6;
constexpr int BAR_TURN = 10;
constexpr int BAR_DONE = 12;

__global__ void __launch_bounds__(384, 1)
afm_kernel(const int* idx_cta, const __nv_bfloat16* __restrict__ W, const __nv_bfloat16* __restrict__ bias,
           const __nv_bfloat16* __restrict__ h, const __nv_bfloat16* __restrict__ pv, const uint2* __restrict__ sched,
           const __nv_bfloat16* __restrict__ table, const int* __restrict__ ii, const int* __restrict__ jj,
           __nv_bfloat16* __restrict__ out, unsigned long long* left, int V
           ) {
  extern __shared__ __align__(1024) uint8_t sm[];
  const int tid = threadIdx.x, lane = tid & 31, t128 = tid & 127;
  const bool assist = blockIdx.x < kAssist;
  uint2 i0, i1;
  {
    uint32_t off;
    asm("slct.b32.s32 %0, %1, %2, %3;" : "=r"(off) : "r"(min(t128, kNS * kF / 2 - 1) * 8),
        "r"((tid & 0x70) + (tid >> 7) * kF * 4), "r"(tid - 256));
    const uint64_t ip = gaddr(idx_cta, blockIdx.x * (kNS * kF * 4) + off);
    if (!assist) i0 = ldg64(ip);
    if (!assist && tid < 256) i1 = ldg64(ip + 8);
  }
  uint32_t pinreg = lane;
  auto pin = [&]() {
    asm volatile("{.reg .pred p; setp.gt.u32 p, %1, 999; @p mov.u32 %0, %clock;}" : "+r"(pinreg) : "r"(tid) : "memory");
  };
  auto keep = [&](uint32_t x) {
    asm volatile("{.reg .pred p; setp.gt.u32 p, %1, 999; @p mov.u32 %0, %clock;}" : "+r"(x) : "r"(tid)); return x;
  };
  pin();
  const int cg = lane & 15, kc = (tid >> 4) - 8;
  const int xl = 2 * cg + (lane >> 4);
  uint64_t hp = gaddr(h, 16 * cg), bp = gaddr(bias, 8 * xl), xp = gaddr(pv, 8 * xl), sp = gaddr(sched, 8 * xl);
  uint64_t wq = gaddr(W, (blockIdx.x & 127) * 256 + 8 * xl);
  asm volatile("" : "+l"(hp), "+l"(bp), "+l"(xp), "+l"(sp), "+l"(wq));
  if (tid < 192) xp = bp;
  if (tid >= 224) xp = sp;
  if (tid >= 256) xp = wq;
  uint4 hv;
  uint2 x2;
  if (tid >= 128) hv = ldg128(hp);
  if (tid >= 128 && tid < 256 + 32 * AFM_WARM) x2 = ldg64(xp);
  if (tid > 999) asm volatile("st.global.b32 [%0], 0;" :: "l"(hp) : "memory");
  pin();
  uint64_t wp = gaddr(W, (32 * (kc >> 2) + 2 * (kc & 3)) * 256 + 16 * cg), gsrc = gaddr(table, 16 * cg);
  asm volatile("" : "+l"(wp), "+l"(gsrc));
  const int warp = __shfl_sync(~0u, tid >> 5, 0), wg = warp >> 2, v = warp & 3;
  uint32_t r[4][4];
  #pragma unroll
  for (int m = 0; m < 8; m++)
    asm volatile("{.reg .b64 z; mov.b64 z, 0; mov.b64 {%0,%1}, z;}" : "=r"(r[m >> 1][2 * (m & 1)]), "=r"(r[m >> 1][2 * (m & 1) + 1]));
  const int lo = t128 < 112, hi = t128 < 96;
  const int first_lo = tid < 256 && lo, first_hi = first_lo && hi;
  uint64_t ga[4];
  auto rows = [&]() {
    i0.x = row_offset(i0.x, V); i0.y = row_offset(i0.y, V);
    ga[0] = gaddr(gsrc, i0.x); ga[1] = gaddr(gsrc, i0.y);
    ga[2] = gaddr(gsrc, row_offset(i1.x, V)); ga[3] = gaddr(gsrc, row_offset(i1.y, V));
  };
  auto gather = [&]() {
    #pragma unroll
    for (int mm = 0; mm < 4; mm++) {
      const int m = (mm >> 1) | (mm & 1) << 1;
      asm volatile("{.reg .pred p; setp.ne.b32 p, %5, 0; @p ld.global.nc.L1::no_allocate.v4.b32 {%0,%1,%2,%3}, [%4];}"
                   : "+r"(r[m][0]), "+r"(r[m][1]), "+r"(r[m][2]), "+r"(r[m][3]) : "l"(ga[m]), "r"(m < 2 ? first_lo : first_hi));
    }
  };
  auto scales = [&]() {
    uint32_t ex[4], g, w;
    lds128(ex, S_G);
    asm volatile("ld.volatile.shared.v2.b32 {%0,%1},[%2];" : "=r"(g), "=r"(w) : "r"(S_G + 32 + (lane & 7) * 8));
    return Scales(ex[1], ex[0], ex[2], __reduce_max_sync(~0u, g) >> 23, __reduce_max_sync(~0u, w) >> 23);
  };
  pin();

  if (__builtin_expect(assist, 0)) {
    constexpr uint32_t kGroup = 17 * 128, S_H = S_B + 16 * kGroup;
    const int c = lane & 3, r8 = lane & 7;
    if (wg == 2) {
      asm volatile("setmaxnreg.dec.sync.aligned.u32 24;");
      const int kg = t128 >> 3;
      const unsigned short pk = *reinterpret_cast<const unsigned short*>(pv + 32 * (kg >> 2) + 2 * (kg & 3) + 8 * (r8 >> 1) + (r8 & 1));
      const uint64_t a = gaddr(W, (8 * (r8 >> 1) + (r8 & 1)) * 256 + kg * 16);
      #pragma unroll
      for (int n = 0; n < 16; n++)
        asm volatile("cp.async.cg.shared.global [%0], [%1], 16;" :: "r"(S_B + n * kGroup + t128 * 16), "l"(a + (32 * (n >> 2) + 2 * (n & 3)) * 256) : "memory");
      asm volatile("st.shared.b16 [%0], %1;" :: "r"(S_B + kg * kGroup + 16 * 128 + r8 * 16), "h"(pk) : "memory");
      sts128(S_H + lane * 16, hv.x, hv.y, hv.z, hv.w);
      asm volatile("cp.async.wait_all;" ::: "memory");
      asm volatile("fence.proxy.async.shared::cta;" ::: "memory");
      bar_arrive(BAR_B, 384);
      return;
    }
    sts32_if(pinreg, pinreg, tid > 999);
    asm volatile("setmaxnreg.inc.sync.aligned.u32 240;");
    asm volatile("mov.u32 %0, %clock;" : "=r"(pinreg) :: "memory");
    const int smp = (32 * blockIdx.x + 4 * warp + (lane >> 4)) * kNS + ((lane >> 2) & 3);
    uint32_t X[2][16], Z[2][16], cb[16];
    auto row = [&](uint32_t (&d)[16], int i) {
      const uint64_t a = gaddr(table, row_offset(i, V) + c * 16);
      #pragma unroll
      for (int q = 0; q < 4; q++)
        asm volatile("ld.global.nc.v4.b32 {%0,%1,%2,%3}, [%4];" : "=r"(d[4 * q]), "=r"(d[4 * q + 1]), "=r"(d[4 * q + 2]), "=r"(d[4 * q + 3]) : "l"(a + q * 64));
    };
    {
      const uint64_t ia = gaddr(idx_cta, (kAssist * kNS + smp) * kF * 4);
      const uint2 j0 = ldg64(ia), j1 = ldg64(ia + 16 * kF * 4);
      #pragma unroll
      for (int j = 0; j < 16; j++) cb[j] = ldg32(gaddr(bias, c * 4) + j * 16);
      row(X[0], j0.x); row(X[1], j1.x); row(Z[0], j0.y); row(Z[1], j1.y);
    }
    uint64_t ia = gaddr(idx_cta, ((kAssist * kNS + smp) * kF + 2) * 4), lp = gaddr(left, smp * 64) - 16;
    int n0 = ldg32(ia), n1 = ldg32(ia + 16 * kF * 4);
    const int v0 = ldg32(ia + (4 * kF - 2) * 4), v1 = ldg32(ia + (20 * kF - 2) * 4);
    const int turn_me = keep(BAR_TURN + wg), turn_ot = keep(BAR_TURN + 1 - wg);
    float acc[68] = {}, e[4] = {}, s0 = 0.f, s1 = 0.f;
    auto hand_over = [&](int on) {
      asm volatile("{.reg .pred p; .reg .b64 u, v; setp.ne.b32 p, %5, 0; mov.b64 u, {%1,%2}; mov.b64 v, {%3,%4};\n"
                   "@p st.relaxed.gpu.global.b64 [%0], u; @p st.relaxed.gpu.global.b64 [%0+1024], v;}"
                   :: "l"(lp), "r"(__float_as_uint(e[0] * 1.4426950408889634f) ^ kLeftTag), "r"(__float_as_uint(s0)),
                      "r"(__float_as_uint(e[2] * 1.4426950408889634f) ^ kLeftTag), "r"(__float_as_uint(s1)), "r"(on) : "memory");
    };
    bar_sync(BAR_B, 384);
    bar_arrive_if(BAR_TURN, 256, wg);
    TL(4);
    #pragma unroll 1
    for (int i = 0; i <= 10; i++) {
      uint32_t A[32], H[32];
      #pragma unroll
      for (int k = 0; k < 16; k++) { A[2 * k] = bmul(X[0][k], Z[0][k]); A[2 * k + 1] = bmul(X[1][k], Z[1][k]); asm volatile("" : "+r"(A[2 * k]), "+r"(A[2 * k + 1])); }
      pin();
      hand_over(c == 0 && i >= 2);
      lp += i == 6 ? 4 * 64 - 4 * 8 : 8;
      if (i == 4) { row(X[0], v0); row(X[1], v1); }
      if (i < 9) { row(Z[0], n0); row(Z[1], n1); }
      ia += i == 3 ? (4 * kF - 4) * 4 : 4;
      if (i < 8) { n0 = ldg32(ia); n1 = ldg32(ia + 16 * kF * 4); }
      bar_sync(turn_me, 256);
      pin();
      #pragma unroll
      for (int j = 0; j < 32; j++)
        asm volatile("{.reg .b32 x; cvt.rn.bf16x2.f32 x, %2, %1; fma.rn.relu.bf16x2 %0, x, %3, %4;}"
                     : "=r"(H[j]) : "f"(acc[2 * j]), "f"(acc[2 * j + 1]), "r"(0x3f803f80u), "r"(cb[j >> 1]));
      s0 = acc[64]; s1 = acc[66];
      asm volatile("" : "+f"(s0), "+f"(s1));
      pin();
      sts32_if(turn_me, turn_me, tid > 999);
      wg_fence();
      #pragma unroll
      for (int ks = 0; ks < 8; ks++) wgmma_n8(e, &H[4 * ks], uint64_t(((S_H + ks * 32) >> 4) | 1 << 16) | uint64_t(8) << 32, ks);
      wg_commit();
      if (i == 10) break;
      #pragma unroll
      for (int ks = 0; ks < 8; ks++)
        wgmma_n136(acc, &A[4 * ks], uint64_t(((S_B + ks * 2 * kGroup) >> 4) | (kGroup >> 4) << 16) | uint64_t(8) << 32, ks);
      wg_commit();
      bar_arrive(turn_ot, 256);
      asm volatile("wgmma.wait_group.sync.aligned 0;" ::: "memory");
      #pragma unroll
      for (int k = 0; k < 68; k++) asm volatile("" : "+f"(acc[k]) :: "memory");
      asm volatile("" : "+f"(e[0]), "+f"(e[1]), "+f"(e[2]), "+f"(e[3]) :: "memory");
    }
    bar_arrive_if(BAR_TURN + 1, 256, !wg);
    asm volatile("wgmma.wait_group.sync.aligned 0;" ::: "memory");
    asm volatile("" : "+f"(e[0]), "+f"(e[1]), "+f"(e[2]), "+f"(e[3]) :: "memory");
    hand_over(c == 0);
    sts32_if(pinreg, pinreg, tid > 999);
    TL(6); TLDUMP();
    return;
  }

  if (wg != 0) {
    TL(15);
    uint4 wv[8];
    #pragma unroll
    for (int i = 0; i < 8; i++) wv[i] = ldg128(wp + (8 * (i >> 1) + (i & 1)) * 256);
    pin();
    uint32_t bd[8];
    #pragma unroll
    for (int i = 0; i < 8; i++) bd[i] = S_B + kc * 2048 + (cg >> 3) * 1024 + ((cg ^ i) & 7) * 16;
    uint32_t ca = S_C + v * 256 + (v < 2 ? (cg >> 2) * 64 + (lane >> 4) * 32 + (cg & 3) * 4 : xl * 8);
    uint32_t cb2 = ca + (v < 2 ? 16 : 4), od = S_RO + t128 * 8 + ((t128 * 79) >> 10) * 24;
    asm volatile("" : "+r"(bd[0]), "+r"(bd[1]), "+r"(bd[2]), "+r"(bd[3]), "+r"(bd[4]), "+r"(bd[5]), "+r"(bd[6]), "+r"(bd[7]),
                 "+r"(ca), "+r"(cb2), "+r"(od));
    pin();
    rows();
    asm volatile("{.reg .pred p; setp.ne.b32 p, %3, 0; @p st.volatile.shared.v2.b32 [%0], {%1,%2};}"
                 :: "r"(od), "r"(i0.x), "r"(i0.y), "r"((int)(tid >= 256)) : "memory");
    asm volatile("" : "+l"(ga[0]), "+l"(ga[1]), "+l"(ga[2]), "+l"(ga[3]));
    pin();
    TL(9);
    const int eh = warp_amax(amax(hv)) >> 23;
    const uint32_t fh = pow2_bf16x2(254 - eh);
    const uint32_t m0 = ((lane < 16 ? hv.x : hv.z) & 0x807f807fu) | 0x3f803f80u, m1 = ((lane < 16 ? hv.y : hv.w) & 0x807f807fu) | 0x3f803f80u;
    hv.x = bmul(hv.x & 0x7f807f80u, fh); hv.y = bmul(hv.y & 0x7f807f80u, fh);
    hv.z = bmul(hv.z & 0x7f807f80u, fh); hv.w = bmul(hv.w & 0x7f807f80u, fh);
    const uint32_t y0 = bmul(v == 1 ? m0 : x2.x, v ? 0x3f803f80u : lane < 16 ? hv.x : hv.z);
    const uint32_t y1 = bmul(v == 1 ? m1 : x2.y, v ? 0x3f803f80u : lane < 16 ? hv.y : hv.w);
    const int e = warp_amax(amax(y0, y1)) >> 23;
    {
      const uint32_t f = pow2_bf16x2((v == 0 ? 146 : v == 1 ? 135 : 139) - e);
      const uint32_t z0 = to_half(y0, f), z1 = to_half(y1, f);
      sts32_if(ca, v == 3 ? x2.x : z0, tid < 256);
      sts32(S_G + (warp - 4) * 4, v == 1 ? eh : e);
      sts32_if(cb2, v == 3 ? x2.y : z1, tid < 256);
      bar_sync(BAR_CONST, 384);
      sts32_if(S_I + (lane & 1) * 16, tau_of(e - 2), tid < 160);
    }
    uint32_t oa = S_RO + (t128 >> 4) * 16, o[4], o3[4];
    lds128(o, oa + 256); lds128(o3, oa + 384);
    uint32_t f0 = bmul(hv.x, pow2_bf16x2(17)), f1 = bmul(hv.y, pow2_bf16x2(17));
    uint32_t f2 = bmul(hv.z, pow2_bf16x2(17)), f3 = bmul(hv.w, pow2_bf16x2(17));
    asm volatile("" : "+r"(f0), "+r"(f1), "+r"(f2), "+r"(f3));
    pin();
    TL(13);
    uint4 cm = wv[0];
    #pragma unroll
    for (int i = 0; i < 8; i++) {
      if (i == AFM_G1) { gather(); pin(); TL(1); }
      if (i) { cm.x = amax(cm.x, wv[i].x); cm.y = amax(cm.y, wv[i].y); cm.z = amax(cm.z, wv[i].z); cm.w = amax(cm.w, wv[i].w); }
      asm volatile("" : "+r"(cm.x), "+r"(cm.y), "+r"(cm.z), "+r"(cm.w));
      sts128(bd[i] + i * 128, to_half(wv[i].x, f0), to_half(wv[i].y, f1), to_half(wv[i].z, f2), to_half(wv[i].w, f3));
      if (i == 3) pin();
    }
    const uint32_t g = warp_amax(amax(amax(bmul(cm.x, hv.x), bmul(cm.y, hv.y)), amax(bmul(cm.z, hv.z), bmul(cm.w, hv.w))));
    sts64(S_G + warp * 8, g, warp_amax(amax(cm)));
    const int other = g >= 126u << 23 || (warp == 4 && e > 137);
    TL(2);

  if (wg == 2) {
    asm volatile("setmaxnreg.dec.sync.aligned.u32 72;");
    const int redo = bar_any(BAR_B, 256, other);
    asm volatile("fence.proxy.async.shared::cta;" ::: "memory");
    uint32_t dst = S_E + (t128 >> 4) * 4 * kRowPitch + cg * 16;
    auto fetch = [&](const uint32_t (&o)[4], int ahead, int on) {
      #pragma unroll
      for (int mm = 0; mm < 4; mm++) {
        const int m = (mm >> 1) | (mm & 1) << 1;
        asm volatile("{.reg .pred p; setp.ne.b32 p, %2, 0; @p cp.async.cg.shared.global [%0], [%1], 16;}"
                     :: "r"(dst + ahead * kSamplePitch + m * kRowPitch), "l"(gaddr(gsrc, o[m])), "r"(on & (m < 2 ? lo : hi)) : "memory");
      }
      asm volatile("cp.async.commit_group;" ::: "memory");
    };
    TL(12);
    int todo = 0xfc | bar_any(BAR_START, 256, redo);
    TL(16);
    fetch(o, 2, 1);
    pin();
    todo |= 2 * bar_any(BAR_START + 1, 256, redo);
    TL(17);
    fetch(o3, 3, 1);
    const Scales sc = scales();
    uint32_t f, wlo, wsz, inf[4];
    auto rescale = [&](int k, int bad) {
      bad |= sc.bad | (k > 14) | (sc.fe + 2 * k > 230);
      inf[0] = sc.tau(2 * k); inf[1] = __float_as_uint(sc.logit(2 * k)); inf[2] = __float_as_uint(sc.dot(2 * k)); inf[3] = bad;
      f = pow2_bf16x2(15 - k);
      wlo = (k + 125) << 23; wsz = bad || k < sc.kb || k < -100 ? 0 : max(sc.ka - 124, 0) << 23;
    };
    rescale(0, sc.fs < 40);
    sts128_if(S_I + lane * 16, inf[0], inf[1], inf[2], inf[3], t128 < 2);
    #pragma unroll 1
    for (int s = 0; s < kNS; s++, dst += kSamplePitch, oa += 128) {
      if (!(todo >> s & 1)) continue;
      if (__builtin_expect(s < 2, 0)) { lds128(o, oa); fetch(o, 0, 1); asm volatile("cp.async.commit_group;" ::: "memory"); }
      lds128(o, oa + 256);
      bar_sync_if(BAR_DONE + v, 160, s == 6 + v);
      asm volatile("cp.async.wait_group 1;" ::: "memory");
      #pragma unroll
      for (int m = 0; m < 2; m++) if (!(AFM_X & 1)) { lds128_if(r[m], dst + m * kRowPitch, lo); lds128_if(r[m + 2], dst + (m + 2) * kRowPitch, hi); }
      fetch(o, 2, s >= 2 && s < kNS - 2 && !(AFM_X & 8));
      uint32_t mx = 0;
      #pragma unroll
      for (int m = 0; m < 4; m++) mx = amax(mx, amax(amax(r[m][0], r[m][1]), amax(r[m][2], r[m][3])));
      mx = amax(mx, mx << 16) & 0x7fff0000u;
      if (__builtin_expect(bar_any(BAR_HELP, 128, !AFM_X && lo && mx - wlo >= wsz), 0)) {
        sts32(S_G + 128 + s * 16 + v * 4, __reduce_max_sync(~0u, mx));
        bar_sync(BAR_HELP, 128);
        mx = __reduce_max_sync(~0u, lds32(S_G + 128 + s * 16 + (lane & 3) * 4));
        const int k = sc.k(mx >> 23);
        rescale(k, (mx != 0) & ((k - ((int)(mx >> 23) - 131) > 7) | (sc.fs + 2 * k < 40)));
      }
      #pragma unroll
      for (int m = 0; m < 4; m++)
        if (AFM_X & 2) sts128_if(dst + m * kRowPitch, r[m][0], r[m][1], r[m][2], r[m][3], (AFM_X & 4) ? tid > 999 : m < 2 ? lo : hi); else
        sts128_if(dst + m * kRowPitch, to_half(r[m][0], f), to_half(r[m][1], f), to_half(r[m][2], f), to_half(r[m][3], f), (AFM_X & 4) ? tid > 999 : m < 2 ? lo : hi);
      sts128_if(S_I + s * 16, inf[0], inf[1], inf[2], inf[3], t128 == 127);
      bar_arrive(s < 2 ? BAR_START + s : BAR_READY + ((s - 2) & 3), 256);
      TL(16 + s);
      if (AFM_PACE && s >= 3) __nanosleep(AFM_PACE);
    }
    TL(3); TLG(0); TL(7);
    int ok;
    {
      int good = (uint32_t)__cvta_generic_to_shared(sm) == kSmemBase;
      #pragma unroll
      for (int k = 0; k < 3; k++) {
        const int q = min(t128 + 128 * k, kP - 1), i = ldg32(gaddr(ii, 4 * q)), j = ldg32(gaddr(jj, 4 * q));
        good &= (unsigned)i < (unsigned)j && (unsigned)j < (unsigned)kF && i * (2 * kF - 3 - i) + 2 * j - 2 == 2 * q;
      }
      ok = !bar_any(BAR_HELP, 128, !good);
    }
    #pragma unroll 1
    for (int s = v; s < kNS; s += 4) {
      const int smp = (blockIdx.x - kAssist) * kNS + s;
      uint2 lv = {kLeftTag ^ 0xff800000u, 0u};
      if (lane < 5) {
        const uint64_t lp = gaddr(left, (smp * 8 + lane) * 8);
        int it = 1 << 20;
        for (;;) {
          asm volatile("{.reg .b64 u; ld.relaxed.gpu.global.b64 u, [%2]; mov.b64 {%0,%1}, u;}" : "=r"(lv.x), "=r"(lv.y) : "l"(lp) : "memory");
          if (lv.x != 0 || --it == 0) break;
          __nanosleep(200);
        }
        asm volatile("st.relaxed.gpu.global.b64 [%0], %1;" :: "l"(lp), "l"(0ull) : "memory");
      }
      __syncwarp();
      if (s == 7) { TL(14); }
      uint64_t op = gaddr(out, smp * 2);
      const uint32_t ta = S_T + (20 * (s & 1) + 5 * (s >> 1)) * kTPitch + lane * 16;
      const int done = (BAR_DONE + s) & 15;
      asm volatile("" : "+l"(op));
      bar_sync_if(s == 7 ? BAR_AUX : done, 160, s >= 2);
      uint32_t info[4], q[5][8];
      lds128(info, S_I + s * 16);
      #pragma unroll
      for (int j = 0; j < 4; j++) { lds128(q[j], ta + j * kTPitch); lds128(q[j] + 4, ta + j * kTPitch + 576); }
      pin();
      const float le = __uint_as_float(info[1]), ds = __uint_as_float(info[2]);
      float2 e[5], d[5];
      auto sums = [&](int j) {
        e[j] = h2f(hadd(hadd(q[j][0], q[j][2]), hadd(q[j][4], q[j][6])));
        d[j] = h2f(hadd(hadd(q[j][1], q[j][3]), hadd(q[j][5], q[j][7])));
        e[j].x = __fmul_rn(e[j].x, le); e[j].y = __fmul_rn(e[j].y, le);
      };
      const int plain = __any_sync(~0u, !ok || info[3] || lv.x == 0);
      const float el = __uint_as_float(lv.x ^ kLeftTag);
      float m = el;
      #pragma unroll
      for (int j = 0; j < 4; j++) { sums(j); m = fmaxf(m, fmaxf(e[j].x, e[j].y)); }
      float den = ex2(el - m), num = 0.f;
      const float nl = den * __uint_as_float(lv.y);
      #pragma unroll
      for (int j = 0; j < 4; j++) {
        const float x = ex2(e[j].x - m), y = ex2(e[j].y - m);
        den += x + y; num = fmaf(x, d[j].x, fmaf(y, d[j].y, num));
      }
      num = fmaf(num, ds, nl);
      den *= 4194304.f;
      asm volatile("" : "+f"(m), "+f"(den), "+f"(num));
      pin();
      if (s == 7) { TL(4); }
      bar_sync_if(done, 160, s == 7);
      lds128(q[4], ta + 4 * kTPitch); lds128(q[4] + 4, ta + 4 * kTPitch + 576);
      if (s == 7) { TL(5); }
      sums(4);
      const float M = warp_max(fmaxf(m, fmaxf(e[4].x, e[4].y)));
      d[4].x *= ds; d[4].y *= ds;
      const uint32_t en = max(__reduce_max_sync(~0u, __float_as_uint(fabsf(num) + fabsf(d[4].x) + fabsf(d[4].y)) & 0x7f800000u), 25u << 23);
      const float up = __uint_as_float((279u << 23) - en);
      const float f = ex2(m - M), x = ex2(e[4].x - M), y = ex2(e[4].y - M);
      const int di = __reduce_add_sync(~0u, __float2int_rn(fmaf(den, f, (x + y) * 4194304.f)));
      const int ni = __reduce_add_sync(~0u, __float2int_rn(fmaf(num * up, f, fmaf(x, d[4].x * up, y * (d[4].y * up)))));
      float rd;
      asm("rcp.approx.ftz.f32 %0, %1;" : "=f"(rd) : "f"((float)di));
      float res = (float)ni * __uint_as_float(en - (3u << 23)) * rd;
      if (__builtin_expect(plain, 0))
        res = plain_sample(idx_cta + (blockIdx.x * kNS + s) * kF, table, V, ii, jj, W, bias, h, pv, lane);
      if (lane == 0) asm volatile("st.global.b16 [%0], %1;" :: "l"(op + (pinreg >> 5)), "h"(__bfloat16_as_ushort(__float2bfloat16(res))) : "memory");
    }
    TL(6); TLG(1); TLDUMP();
    return;
  }
    bar_any(BAR_B, 256, other);
  } else {
    rows();
    gather();
    pin();
    TL(11);
    bar_sync(BAR_CONST, 384);
  }
  {
    const int c = lane & 3, quad = t128 >> 2;
    uint32_t cb[16], ch[16], cp[16], c16 = keep(c * 16);
    uint2 sch;
    asm volatile("ld.volatile.shared.v2.b32 {%0,%1},[%2];" : "=r"(sch.x), "=r"(sch.y) : "r"(S_C + 768 + quad * 8));
    #pragma unroll
    for (int i = 0; i < 4; i++) {
      lds128(&cp[4 * i], S_C + 512 + i * 64 + c16);
      lds128(&cb[4 * i], S_C + i * 64 + c16);
      lds128(&ch[4 * i], S_C + 256 + i * 64 + c16);
    }
    TL(7);
    sts32_if(pinreg, pinreg, tid > 999);
    asm volatile("setmaxnreg.inc.sync.aligned.u32 216;");
    asm volatile("mov.u32 %0, %clock;" : "=r"(pinreg) :: "memory");

    uint32_t acc[32], A[32], S0, S1, T0, T1;
    auto mma = [&](int q) {
      wg_fence();
      #pragma unroll
      for (int ks = 2 * q; ks < 2 * q + 2; ks++) {
        const uint64_t desc = uint64_t(((S_B + ks * 4096) >> 4) | ((1024 >> 4) << 16)) | (uint64_t((2048 >> 4) | (1 << 30)) << 32);
        if (ks == 0) wgmma_n128<false>(acc, &A[0], desc); else wgmma_n128<true>(acc, &A[4 * ks], desc);
      }
    };
    auto dots = [&](int q) {
      #pragma unroll
      for (int r = 4 * q; r < 4 * q + 4; r++) {
        S0 = r ? hfma(A[2 * r], cp[r], S0) : hmul(A[0], cp[0]);
        S1 = r ? hfma(A[2 * r + 1], cp[r], S1) : hmul(A[1], cp[0]);
      }
    };
    auto wait = [&]() {
      asm volatile("wgmma.wait_group.sync.aligned 0;" ::: "memory");
      #pragma unroll
      for (int i = 0; i < 32; i++) asm volatile("" : "+r"(acc[i]) :: "memory");
    };
    auto logits = [&](uint32_t tau) {
      #pragma unroll
      for (int j = 0; j < 16; j++) {
        const uint32_t y0 = hfma_relu(cb[j], tau, acc[2 * j]), y1 = hfma_relu(cb[j], tau, acc[2 * j + 1]);
        T0 = j ? hfma(y0, ch[j], T0) : hmul(y0, ch[0]);
        T1 = j ? hfma(y1, ch[j], T1) : hmul(y1, ch[0]);
      }
    };

    uint32_t tv = 0, sv = 0;
    auto fold_to = [&](uint32_t& d, uint32_t a, uint32_t b) {
      asm volatile("{.reg .pred p; setp.gt.u32 p, %3, 999; @!p add.rn.f16x2 %0, %1, %2;}"
                   : "+r"(d) : "r"(__byte_perm(a, b, 0x5410)), "r"(__byte_perm(a, b, 0x7632)), "r"(tid));
    };

    uint32_t R[5][16], ad[8];
    const uint32_t base = S_E + wg * kSamplePitch;
    #pragma unroll
    for (int i = 0; i < 8; i++) ad[i] = base + c16 + __byte_perm(i < 4 ? sch.x : sch.y, 0, 0x4440 + (i & 3)) * 64;
    uint32_t tb = S_T + 20 * wg * kTPitch + quad * 16 + (c & 1) * 8 + (c >> 1) * 576;
    const int mixed = quad >= 24;
    {
      uint32_t dst = base + (t128 >> 4) * 4 * kRowPitch + cg * 16, id = BAR_START + wg, mx = lo ? 0 : 0x3f80;
      const uint32_t f = pow2_bf16x2(15);
      asm volatile("" : "+r"(ad[0]), "+r"(ad[1]), "+r"(ad[2]), "+r"(ad[3]), "+r"(ad[4]), "+r"(ad[5]), "+r"(ad[6]), "+r"(ad[7]), "+r"(tb), "+r"(dst), "+r"(id), "+r"(mx));
      pin();
      #pragma unroll
      for (int i = 0; i < 8; i++) ad[i] = keep(ad[i]);
      tb = keep(tb); dst = keep(dst); id = keep(id); mx = keep(mx);
      TL(3);
      #pragma unroll
      for (int m = 0; m < 4; m++) {
        mx = amax(mx, amax(amax(r[m][0], r[m][1]), amax(r[m][2], r[m][3])));
        sts128_if(dst + m * kRowPitch, to_half(r[m][0], f), to_half(r[m][1], f), to_half(r[m][2], f), to_half(r[m][3], f), m < 2 ? lo : hi);
      }
      TL(10);
      const int redo = bar_any(id, 256, (amax(mx, mx << 16) & 0x7fff0000u) - (125u << 23) >= 5u << 23);
      bar_sync_if(id, 256, redo);
    }
    bar_sync_if(BAR_CONST, 256, wg);
    TLB(4);
    #pragma unroll
    for (int q = 0; q < 4; q++) {
      #pragma unroll
      for (int i = 0; i < 3; i++) lds128(&R[i][4 * q], ad[i] + q * 64);
      if (q == 2) bar_arrive_if(BAR_CONST, 256, wg == 0);
    }
    const int turn_me = keep(BAR_TURN + wg), turn_ot = keep(BAR_TURN + 1 - wg);
    bar_sync_if(BAR_TURN + 1, 256, wg);
    TL(5);
    uint32_t eo = 0, to = 0, io = S_I + wg * 16, ready = keep(BAR_READY + wg), done = keep(BAR_DONE - 2 + wg);
    #pragma unroll 1
    for (int run = 0; run < 4 + AFM_EXTRA; run++) {
      const int more = run < 3 + AFM_EXTRA, adv = !AFM_EXTRA || run < 1 || run >= 1 + AFM_EXTRA;
      uint32_t tau;
      asm volatile("{.reg .pred p; setp.ne.b32 p, %3, 0; @p st.volatile.shared.v2.b32 [%0], {%1,%2};}"
                   :: "r"(tb + to - kTPitch), "r"(tv), "r"(sv), "r"(run) : "memory");
      pin();
      bar_arrive_if(done, 160, AFM_EXTRA ? run == 1 || run > 1 + AFM_EXTRA : run);
      #pragma unroll
      for (int j = 0; j < 5; j++) {
        constexpr int kz[5] = {2, 3, 4, 0, 3}, kx[5] = {0, 1, 1, 1, 0}, ky[5] = {1, 2, 2, 4, 4}, kn[5] = {3, 4, 2, 1, 0};
        const int z = kz[j], x = kx[j], y = ky[j], n = kn[j];
        auto muls = [&](int q) {
          #pragma unroll
          for (int r = 4 * q; r < 4 * q + 4; r++) { A[2 * r] = hmul(R[z][r], R[x][r]); A[2 * r + 1] = hmul(R[z][r], R[y][r]); }
        };
        auto load = [&](int q) {
          constexpr int kNext = AFM_EXTRA ? 0 : 2 * kSamplePitch;
          if (j < 2) lds128(&R[n][4 * q], ad[n] + eo + q * 64);
          else lds128_if(&R[n][4 * q], ad[n] + eo + kNext + q * 64, j == 2 ? more && run : more);
          if (j == 4) lds128_if(&R[2][4 * q], ad[2] + kNext + q * 64, !run);
          if (j < 3) lds128_if(&R[1][4 * q], ad[5 + j] + eo + q * 64, mixed);
        };
        muls(0); pin();
        mma(0);
        muls(1); dots(0); pin();
        mma(1);
        if (AFM_ARR == 1) pin();
        if (AFM_ARR == 1) { if (j < 4) bar_arrive(turn_ot, 256); else bar_arrive_if(turn_ot, 256, more || wg == 0); }
        load(0);
        if (j == 0) tau = lds32(io);
        muls(2); load(1); dots(1); load(2); pin();
        mma(2);
        muls(3); pin();
        if (AFM_ARR == 2) { if (j < 4) bar_arrive(turn_ot, 256); else bar_arrive_if(turn_ot, 256, more || wg == 0); }
        load(3);
        dots(2); dots(3);
        fold_to(sv, S0, S1);
        pin();
        mma(3);
        wg_commit();
        if (j == 1) bar_sync_if(ready, 256, more && adv && run);
        if (j == 2) bar_sync_if(ready, 256, !run);
        if (j < 4) bar_sync(turn_me, 256); else bar_sync_if(turn_me, 256, more);
        pin();
        wait();
        logits(tau);
        fold_to(tv, T0, T1);
        if (j < 4) sts64(tb + to + j * kTPitch, tv, sv);
        if (j == 3) bar_arrive_if(BAR_AUX, 160, !more && wg);
        if (j == 3 && adv) { done = (done + 2) & 15; ready ^= 14; }
        pin();
      }
      if (adv) { eo += 2 * kSamplePitch; to += 5 * kTPitch; io += 32; }
    }
    sts64(tb + 19 * kTPitch, tv, sv);
    bar_arrive(done, 160);
    sts32_if(pinreg, pinreg, tid > 999);
    TL(6);
    TLDUMP();
  }
}

}

extern "C" void kernel_launch(void* const* d_in, const int* in_sizes, int n_in, void* d_out, int out_size) {
  (void)n_in; (void)out_size;
  void *sched = nullptr, *left = nullptr;
  cudaGetSymbolAddress(&sched, kSched);
  cudaGetSymbolAddress(&left, gLeft);
  cudaFuncSetAttribute(afm_kernel, cudaFuncAttributeMaxDynamicSharedMemorySize, kSmemBytes);
  afm_kernel<<<kB / kNS + kAssist, 384, kSmemBytes>>>(
      (const int*)d_in[0] - kAssist * kNS * kF, (const __nv_bfloat16*)d_in[4], (const __nv_bfloat16*)d_in[5],
      (const __nv_bfloat16*)d_in[6], (const __nv_bfloat16*)d_in[7], (const uint2*)sched,
      (const __nv_bfloat16*)d_in[1], (const int*)d_in[2], (const int*)d_in[3], (__nv_bfloat16*)d_out,
      (unsigned long long*)left, in_sizes[1] / kD
      );
}
```

```cpp
#include <cuda_runtime.h>
#include <cuda_bf16.h>
#include <cuda_fp16.h>
#include <stdint.h>

#define AFM_G1 0
#define AFM_WARM 1
#define AFM_X 0
#define AFM_ARR 2
#define AFM_C1 6
#define AFM_DA 0
#define AFM_GATE 2
#define AFM_PEEL 0
#define AFM_SMALL 0
#define AFM_F3 1
#define AFM_D1 700
#define AFM_UNG 2
#define AFM_I3 0
#define AFM_SPLIT 0
#define AFM_DEFER 1
#define AFM_LATE 0
#define AFM_HG 3
#define AFM_RDY 0
#define AFM_PACE 0
#define AFM_EXTRA 0

namespace {

constexpr int kB = 1024, kF = 26, kP = 325, kD = 128, kNS = 8;
constexpr int kAssist = 4;
constexpr int kRowPitch = 320;
constexpr int kSamplePitch = kF * kRowPitch;
constexpr int kTPitch = 1152;
constexpr uint32_t kSmemBase = 1024;
constexpr uint32_t S_B = kSmemBase;
constexpr uint32_t S_C = S_B + 32768;
constexpr uint32_t S_G = S_C + 1024;
constexpr uint32_t S_I = S_G + 256;
constexpr uint32_t S_F = S_I + 128;
constexpr uint32_t S_RO = S_F + 128;
constexpr uint32_t S_E = S_RO + 1280;
constexpr uint32_t S_T = S_E + kNS * kSamplePitch;
constexpr uint32_t S_LEAD = S_T + 39 * kTPitch;
constexpr uint32_t S_END = S_T + 40 * kTPitch;
constexpr int kSmemBytes = S_END - kSmemBase;

__device__ const uint2 kSched[32] = {
  {0x05555028u,0x5050506eu}, {0x5a323705u,0x37373773u}, {0x64551932u,0x1919190au}, {0x4b5a2823u,0x28282819u},
  {0x695a460au,0x4646466eu}, {0x78554b41u,0x4b4b4b69u}, {0x0a144b2du,0x4b4b4b73u}, {0x7d233c0au,0x3c3c3c50u},
  {0x6e143723u,0x37373778u}, {0x73195046u,0x50505078u}, {0x2d5a500fu,0x50505041u}, {0x6e0f4b32u,0x4b4b4b3cu},
  {0x69145032u,0x5050501eu}, {0x642d0523u,0x05050569u}, {0x235f4632u,0x46464641u}, {0x1e5f192du,0x1919196eu},
  {0x2d554637u,0x4646463cu}, {0x5a555f14u,0x5f5f5f7du}, {0x69190f37u,0x0f0f0f7du}, {0x64460f28u,0x0f0f0f14u},
  {0x0514193cu,0x19191941u}, {0x1e410a37u,0x0a0a0a28u}, {0x7832282du,0x2828287du}, {0x5f0f050au,0x05050578u},
  {0x3c5a001eu,0x46002878u}, {0x5523001eu,0x7373730fu}, {0x64500037u,0x005f5a4bu}, {0x735f373cu,0x00782364u},
  {0x6e005541u,0x64697d73u}, {0x695f5028u,0x73323c00u}, {0x46051e4bu,0x0073007du}, {0x7d002d1eu,0x4b6e4164u},
};
__device__ unsigned long long gLeft[kB * 8];
constexpr uint32_t kLeftTag = 0x7fc5a5a5u;

template <bool kAccumulate>
__device__ __forceinline__ void wgmma_n128(uint32_t (&d)[32], const uint32_t* a, uint64_t desc) {
  if (kAccumulate) {
    asm volatile("wgmma.mma_async.sync.aligned.m64n128k16.f16.f16.f16 "
      "{%0, %1, %2, %3, %4, %5, %6, %7, %8, %9, %10, %11, %12, %13, %14, %15, %16, %17, %18, %19, %20, %21, %22, %23, %24, %25, %26, %27, %28, %29, %30, %31}, "
      "{%32, %33, %34, %35}, %36, 1, 1, 1, 1;"
      : "+r"(d[0]), "+r"(d[1]), "+r"(d[2]), "+r"(d[3]), "+r"(d[4]), "+r"(d[5]), "+r"(d[6]), "+r"(d[7]), "+r"(d[8]), "+r"(d[9]), "+r"(d[10]), "+r"(d[11]), "+r"(d[12]), "+r"(d[13]), "+r"(d[14]), "+r"(d[15]), "+r"(d[16]), "+r"(d[17]), "+r"(d[18]), "+r"(d[19]), "+r"(d[20]), "+r"(d[21]), "+r"(d[22]), "+r"(d[23]), "+r"(d[24]), "+r"(d[25]), "+r"(d[26]), "+r"(d[27]), "+r"(d[28]), "+r"(d[29]), "+r"(d[30]), "+r"(d[31])
      : "r"(a[0]), "r"(a[1]), "r"(a[2]), "r"(a[3]), "l"(desc));
  } else {
    asm volatile("wgmma.mma_async.sync.aligned.m64n128k16.f16.f16.f16 "
      "{%0, %1, %2, %3, %4, %5, %6, %7, %8, %9, %10, %11, %12, %13, %14, %15, %16, %17, %18, %19, %20, %21, %22, %23, %24, %25, %26, %27, %28, %29, %30, %31}, "
      "{%32, %33, %34, %35}, %36, 0, 1, 1, 1;"
      : "=r"(d[0]), "=r"(d[1]), "=r"(d[2]), "=r"(d[3]), "=r"(d[4]), "=r"(d[5]), "=r"(d[6]), "=r"(d[7]), "=r"(d[8]), "=r"(d[9]), "=r"(d[10]), "=r"(d[11]), "=r"(d[12]), "=r"(d[13]), "=r"(d[14]), "=r"(d[15]), "=r"(d[16]), "=r"(d[17]), "=r"(d[18]), "=r"(d[19]), "=r"(d[20]), "=r"(d[21]), "=r"(d[22]), "=r"(d[23]), "=r"(d[24]), "=r"(d[25]), "=r"(d[26]), "=r"(d[27]), "=r"(d[28]), "=r"(d[29]), "=r"(d[30]), "=r"(d[31])
      : "r"(a[0]), "r"(a[1]), "r"(a[2]), "r"(a[3]), "l"(desc));
  }
}

__device__ __forceinline__ void wgmma_n136(float (&d)[68], const uint32_t* a, uint64_t desc, int accumulate) {
  asm volatile("{.reg .pred p; setp.ne.b32 p, %73, 0; wgmma.mma_async.sync.aligned.m64n136k16.f32.bf16.bf16 "
    "{%0, %1, %2, %3, %4, %5, %6, %7, %8, %9, %10, %11, %12, %13, %14, %15, %16, %17, %18, %19, %20, %21, %22, %23, %24, %25, %26, %27, %28, %29, %30, %31, %32, %33, %34, %35, %36, %37, %38, %39, %40, %41, %42, %43, %44, %45, %46, %47, %48, %49, %50, %51, %52, %53, %54, %55, %56, %57, %58, %59, %60, %61, %62, %63, %64, %65, %66, %67}, "
    "{%68, %69, %70, %71}, %72, p, 1, 1, 1;}"
    : "+f"(d[0]), "+f"(d[1]), "+f"(d[2]), "+f"(d[3]), "+f"(d[4]), "+f"(d[5]), "+f"(d[6]), "+f"(d[7]), "+f"(d[8]), "+f"(d[9]), "+f"(d[10]), "+f"(d[11]), "+f"(d[12]), "+f"(d[13]), "+f"(d[14]), "+f"(d[15]), "+f"(d[16]), "+f"(d[17]), "+f"(d[18]), "+f"(d[19]), "+f"(d[20]), "+f"(d[21]), "+f"(d[22]), "+f"(d[23]), "+f"(d[24]), "+f"(d[25]), "+f"(d[26]), "+f"(d[27]), "+f"(d[28]), "+f"(d[29]), "+f"(d[30]), "+f"(d[31]), "+f"(d[32]), "+f"(d[33]), "+f"(d[34]), "+f"(d[35]), "+f"(d[36]), "+f"(d[37]), "+f"(d[38]), "+f"(d[39]), "+f"(d[40]), "+f"(d[41]), "+f"(d[42]), "+f"(d[43]), "+f"(d[44]), "+f"(d[45]), "+f"(d[46]), "+f"(d[47]), "+f"(d[48]), "+f"(d[49]), "+f"(d[50]), "+f"(d[51]), "+f"(d[52]), "+f"(d[53]), "+f"(d[54]), "+f"(d[55]), "+f"(d[56]), "+f"(d[57]), "+f"(d[58]), "+f"(d[59]), "+f"(d[60]), "+f"(d[61]), "+f"(d[62]), "+f"(d[63]), "+f"(d[64]), "+f"(d[65]), "+f"(d[66]), "+f"(d[67])
    : "r"(a[0]), "r"(a[1]), "r"(a[2]), "r"(a[3]), "l"(desc), "r"(accumulate));
}
__device__ __forceinline__ void wgmma_n8(float (&d)[4], const uint32_t* a, uint64_t desc, int accumulate) {
  asm volatile("{.reg .pred p; setp.ne.b32 p, %9, 0; wgmma.mma_async.sync.aligned.m64n8k16.f32.bf16.bf16 "
    "{%0, %1, %2, %3}, {%4, %5, %6, %7}, %8, p, 1, 1, 0;}"
    : "+f"(d[0]), "+f"(d[1]), "+f"(d[2]), "+f"(d[3])
    : "r"(a[0]), "r"(a[1]), "r"(a[2]), "r"(a[3]), "l"(desc), "r"(accumulate));
}

__device__ __forceinline__ uint32_t hmul(uint32_t a, uint32_t b) {
  uint32_t r; asm volatile("mul.rn.f16x2 %0,%1,%2;" : "=r"(r) : "r"(a), "r"(b)); return r;
}
__device__ __forceinline__ uint32_t hadd(uint32_t a, uint32_t b) {
  uint32_t r; asm volatile("add.rn.f16x2 %0,%1,%2;" : "=r"(r) : "r"(a), "r"(b)); return r;
}
__device__ __forceinline__ uint32_t hfma(uint32_t a, uint32_t b, uint32_t c) {
  uint32_t r; asm volatile("fma.rn.f16x2 %0,%1,%2,%3;" : "=r"(r) : "r"(a), "r"(b), "r"(c)); return r;
}
__device__ __forceinline__ uint32_t hfma_relu(uint32_t a, uint32_t b, uint32_t c) {
  uint32_t r; asm volatile("fma.rn.relu.f16x2 %0,%1,%2,%3;" : "=r"(r) : "r"(a), "r"(b), "r"(c)); return r;
}
__device__ __forceinline__ float2 h2f(uint32_t v) { return __half22float2(*reinterpret_cast<__half2*>(&v)); }
__device__ __forceinline__ uint32_t bmul(uint32_t a, uint32_t b) {
  uint32_t r; asm("mul.rn.bf16x2 %0,%1,%2;" : "=r"(r) : "r"(a), "r"(b)); return r;
}
__device__ __forceinline__ uint32_t amax(uint32_t a, uint32_t b) {
  uint32_t r; asm("max.NaN.xorsign.abs.bf16x2 %0,%1,%2;" : "=r"(r) : "r"(a), "r"(b)); return r;
}
__device__ __forceinline__ uint32_t amax(const uint4& v) { return amax(amax(v.x, v.y), amax(v.z, v.w)); }
__device__ __forceinline__ uint32_t warp_amax(uint32_t m) { return __reduce_max_sync(~0u, amax(m, m << 16) & 0x7fff0000u); }
__device__ __forceinline__ uint32_t pow2_bf16x2(int field) { return field * 0x00800080u; }
__device__ __forceinline__ uint32_t to_half(uint32_t x, uint32_t f) {
  const uint32_t y = bmul(x, f);
  return y + 7u * (y & 0x0fff0fffu);
}
__device__ __forceinline__ void lds128(uint32_t* r, uint32_t addr) {
  asm volatile("ld.volatile.shared.v4.b32 {%0,%1,%2,%3},[%4];"
               : "=r"(r[0]), "=r"(r[1]), "=r"(r[2]), "=r"(r[3]) : "r"(addr));
}
__device__ __forceinline__ void lds128_if(uint32_t* r, uint32_t addr, int pr) {
  asm volatile("{.reg .pred p; setp.ne.b32 p, %5, 0; @p ld.volatile.shared.v4.b32 {%0,%1,%2,%3},[%4];}"
               : "+r"(r[0]), "+r"(r[1]), "+r"(r[2]), "+r"(r[3]) : "r"(addr), "r"(pr));
}
__device__ __forceinline__ uint32_t lds32(uint32_t addr) {
  uint32_t r; asm volatile("ld.volatile.shared.b32 %0,[%1];" : "=r"(r) : "r"(addr)); return r;
}
__device__ __forceinline__ void sts32(uint32_t addr, uint32_t a) {
  asm volatile("st.volatile.shared.b32 [%0], %1;" :: "r"(addr), "r"(a) : "memory");
}
__device__ __forceinline__ void sts64(uint32_t addr, uint32_t a, uint32_t b) {
  asm volatile("st.volatile.shared.v2.b32 [%0], {%1,%2};" :: "r"(addr), "r"(a), "r"(b) : "memory");
}
__device__ __forceinline__ void sts128(uint32_t addr, uint32_t a, uint32_t b, uint32_t c, uint32_t d) {
  asm volatile("st.volatile.shared.v4.b32 [%0], {%1,%2,%3,%4};" :: "r"(addr), "r"(a), "r"(b), "r"(c), "r"(d) : "memory");
}
__device__ __forceinline__ void sts32_if(uint32_t addr, uint32_t a, int pr) {
  asm volatile("{.reg .pred p; setp.ne.b32 p, %2, 0; @p st.volatile.shared.b32 [%0], %1;}" :: "r"(addr), "r"(a), "r"(pr) : "memory");
}
__device__ __forceinline__ void sts128_if(uint32_t addr, uint32_t a, uint32_t b, uint32_t c, uint32_t d, int pr) {
  asm volatile("{.reg .pred p; setp.ne.b32 p, %5, 0; @p st.volatile.shared.v4.b32 [%0], {%1,%2,%3,%4};}"
               :: "r"(addr), "r"(a), "r"(b), "r"(c), "r"(d), "r"(pr) : "memory");
}
__device__ __forceinline__ uint64_t gaddr(uint64_t base, uint32_t off) {
  uint64_t a;
  asm("{.reg .b32 lo, hi; add.cc.u32 lo, %1, %3; addc.u32 hi, %2, 0; mov.b64 %0, {lo, hi};}"
      : "=l"(a) : "r"((uint32_t)base), "r"((uint32_t)(base >> 32)), "r"(off));
  return a;
}
__device__ __forceinline__ uint64_t gaddr(const void* base, uint32_t off) { return gaddr((uint64_t)base, off); }
__device__ __forceinline__ uint4 ldg128(uint64_t p) {
  uint4 v; asm volatile("ld.global.v4.b32 {%0,%1,%2,%3}, [%4];" : "=r"(v.x), "=r"(v.y), "=r"(v.z), "=r"(v.w) : "l"(p));
  return v;
}
__device__ __forceinline__ uint2 ldg64(uint64_t p) {
  uint2 v; asm volatile("ld.global.v2.b32 {%0,%1}, [%2];" : "=r"(v.x), "=r"(v.y) : "l"(p)); return v;
}
__device__ __forceinline__ int ldg32(uint64_t p) {
  int v; asm volatile("ld.global.b32 %0, [%1];" : "=r"(v) : "l"(p)); return v;
}
__device__ __forceinline__ uint32_t row_offset(int r, int V) { return __viaddmin_u32(r, V, r) << 8; }
__device__ __forceinline__ float ex2(float x) { float r; asm("ex2.approx.ftz.f32 %0, %1;" : "=f"(r) : "f"(x)); return r; }
__device__ __forceinline__ float warp_max(float m) {
  int i = __float_as_int(m);
  i ^= (i >> 31) & 0x7fffffff;
  i = __reduce_max_sync(~0u, i);
  i ^= (i >> 31) & 0x7fffffff;
  return __int_as_float(i);
}
__device__ __forceinline__ void bar_sync(int id, int n) { asm volatile("bar.sync %0, %1;" :: "r"(id), "r"(n) : "memory"); }
__device__ __forceinline__ void bar_arrive(int id, int n) { asm volatile("bar.arrive %0, %1;" :: "r"(id), "r"(n) : "memory"); }
__device__ __forceinline__ void bar_sync_if(int id, int n, int pr) {
  asm volatile("{.reg .pred p; setp.ne.b32 p, %2, 0; @p bar.sync %0, %1;}" :: "r"(id), "r"(n), "r"(pr) : "memory");
}
__device__ __forceinline__ void bar_arrive_if(int id, int n, int pr) {
  asm volatile("{.reg .pred p; setp.ne.b32 p, %2, 0; @p bar.arrive %0, %1;}" :: "r"(id), "r"(n), "r"(pr) : "memory");
}
__device__ __forceinline__ int bar_any(int id, int n, int pr) {
  int r;
  asm volatile("{.reg .pred p, q; setp.ne.b32 p, %3, 0; bar.red.or.pred q, %1, %2, p; selp.b32 %0, 1, 0, q;}"
               : "=r"(r) : "r"(id), "r"(n), "r"(pr) : "memory");
  return __any_sync(~0u, r);
}
__device__ __forceinline__ void wg_fence() { asm volatile("wgmma.fence.sync.aligned;" ::: "memory"); }
__device__ __forceinline__ void wg_commit() { asm volatile("wgmma.commit_group.sync.aligned;" ::: "memory"); }

__device__ __forceinline__ uint32_t tau_of(int field) {
  uint32_t r; asm("cvt.rn.f16x2.f32 %0, %1, %1;" : "=r"(r) : "f"(__int_as_float(max(field, 0) << 23))); return r;
}
struct Scales {
  int ka, kb, ft, fe, fs, bad;
  __device__ __forceinline__ Scales(int eh, int eb, int ep, int eg, int ew)
      : ka(126 + min((131 - eg) >> 1, 5)), kb((eb - 136) >> 1), ft(eb - 2), fe(eh + 5), fs(ep + 3),
        bad((eg > 133) | (eg < 114 && ew) | (ew - eg > 10) | (eb > 145) | (ep > 138) | (eh > 253)) {}
  __device__ __forceinline__ int k(int em) const { return max(em - ka, kb); }
  __device__ __forceinline__ uint32_t tau(int n) const { return tau_of(ft - n); }
  __device__ __forceinline__ float logit(int n) const { return __int_as_float(max(fe + n, 0) << 23) * 1.4426950408889634f; }
  __device__ __forceinline__ float dot(int n) const { return __int_as_float(max(fs + n, 0) << 23); }
};

#define TL(i)
#define TLB(i)
#define TLA(i)
#define TLG(i)
#define TLDUMP()

#define LT(i)
__device__ __noinline__ float plain_sample(const int* rows, const __nv_bfloat16* table, int V, const int* ii, const int* jj,
                                           const __nv_bfloat16* W, const __nv_bfloat16* bias,
                                           const __nv_bfloat16* h, const __nv_bfloat16* pv, int lane) {
  float m = -INFINITY, den = 0.f, num = 0.f;
  #pragma unroll 1
  for (int p = 0; p < kP; p++) {
    int i = ii[p], j = jj[p];
    if (i < 0) i += kF;
    if (j < 0) j += kF;
    const __nv_bfloat16* ei = table + row_offset(rows[min(max(i, 0), kF - 1)], V) / 2;
    const __nv_bfloat16* ej = table + row_offset(rows[min(max(j, 0), kF - 1)], V) / 2;
    float x[4] = {0.f, 0.f, 0.f, 0.f}, s = 0.f;
    #pragma unroll 4
    for (int d = 0; d < kD; d++) {
      const float pr = __bfloat162float(__hmul(ei[d], ej[d]));
      s = fmaf(pr, __bfloat162float(pv[d]), s);
      #pragma unroll
      for (int k = 0; k < 4; k++) x[k] = fmaf(pr, __bfloat162float(W[d * kD + lane + 32 * k]), x[k]);
    }
    float e = 0.f;
    #pragma unroll
    for (int k = 0; k < 4; k++) {
      const float y = x[k] + __bfloat162float(bias[lane + 32 * k]);
      e = fmaf(0.5f * (y + fabsf(y)), __bfloat162float(h[lane + 32 * k]), e);
    }
    #pragma unroll
    for (int o = 16; o; o >>= 1) e += __shfl_xor_sync(~0u, e, o);
    const float mn = e > m || e != e ? e : m, f = __expf(m - mn), w = __expf(e - mn);
    den = den * f + w; num = num * f + w * s; m = mn;
  }
  return num / den;
}

constexpr int BAR_CONST = 0;
constexpr int BAR_B = 1;
constexpr int BAR_START = 2;
constexpr int BAR_HELP = 4;
constexpr int BAR_AUX = 5;
constexpr int BAR_READY = 6;
constexpr int BAR_TURN = 10;
constexpr int BAR_DONE = 12;

struct Vectors { const __nv_bfloat16* p[4]; };

__global__ void __launch_bounds__(512, 1)
afm_kernel(const int* __restrict__ idx, const __nv_bfloat16* __restrict__ W, const __grid_constant__ Vectors vec,
           const __nv_bfloat16* __restrict__ table, const int* __restrict__ ii, const int* __restrict__ jj,
           __nv_bfloat16* __restrict__ out, unsigned long long* left, int V
           ) {
  extern __shared__ __align__(1024) uint8_t sm[];
  const int tid = threadIdx.x, lane = tid & 31, t128 = tid & 127;
  const bool assist = blockIdx.x < kAssist;
  const int cta = (blockIdx.x - kAssist) & (kB / kNS - 1);
  const __nv_bfloat16 *bias = vec.p[0], *h = vec.p[1], *pv = vec.p[2];
  const uint64_t ip = gaddr(idx + cta * (kNS * kF), (tid & 0x70) + (tid >> 7) * kF * 4);
  uint2 i0, i1;
  if (tid < 512 - 128 * AFM_I3) { i0 = ldg64(ip); i1 = ldg64(ip + 8); }
  uint32_t pinreg = lane;
  const int never = __any_sync(~0u, tid > 999);
  auto pin = [&]() {
    asm volatile("{.reg .pred p; setp.ne.b32 p, %1, 0; @p mov.u32 %0, %clock;}" : "+r"(pinreg) : "r"(never) : "memory");
  };
  auto keep = [&](uint32_t x) {
    asm volatile("{.reg .pred p; setp.ne.b32 p, %1, 0; @p mov.u32 %0, %clock;}" : "+r"(x) : "r"(never)); return x;
  };
  pin();
  const int warp = __shfl_sync(~0u, tid >> 5, 0), wg = warp >> 2, v = warp & 3;
  const int cg = lane & 15, kc = (tid >> 4) - 16, xl = 2 * cg + (lane >> 4);
  uint4 hv;
  uint2 x2;
  uint64_t hp = gaddr(h, 16 * cg);
  asm volatile("" : "+l"(hp));
  if (tid >= 256) hv = ldg128(hp);
  asm volatile("{.reg .pred p; setp.ge.u32 p, %2, 496; @p cp.async.cg.shared.global [%0], [%1], 16;}"
               :: "r"(S_T + 16 * cg), "l"(gaddr(W + cta * kD, 16 * cg)), "r"(tid) : "memory");
  pin();
  uint64_t xp = gaddr(vec.p[v], 8 * xl);
  asm volatile("" : "+l"(xp));
  if (tid >= 384) x2 = ldg64(xp);
  if (never) asm volatile("st.global.b32 [%0], 0;" :: "l"(ip) : "memory");
  pin();
  uint64_t wp = gaddr(W, (32 * (kc >> 2) + 2 * (kc & 3)) * 256 + 16 * cg);
  asm volatile("" : "+l"(wp));
  uint32_t r[4][4];
  int t, lo, hi;
  uint64_t gsrc, ga[4];
  auto idle = [&]() {
    pin();
    t = keep(tid);
    lo = (t & 127) < 112; hi = (t & 127) < 96;
    gsrc = gaddr(table, 16 * (t & 15));
    asm volatile("" : "+l"(gsrc));
  };
  auto rows = [&]() {
    ga[0] = gaddr(gsrc, row_offset(i0.x, V)); ga[1] = gaddr(gsrc, row_offset(i0.y, V));
    ga[2] = gaddr(gsrc, row_offset(i1.x, V)); ga[3] = gaddr(gsrc, row_offset(i1.y, V));
  };
  auto gather = [&](int pa, int pb) {
    #pragma unroll
    for (int mm = 0; mm < 4; mm++) {
      const int m = (mm >> 1) | (mm & 1) << 1;
      asm volatile("{.reg .pred p; setp.ne.b32 p, %5, 0; @p ld.global.nc.L1::no_allocate.v4.b32 {%0,%1,%2,%3}, [%4];}"
                   : "+r"(r[m][0]), "+r"(r[m][1]), "+r"(r[m][2]), "+r"(r[m][3]) : "l"(ga[m]), "r"(m < 2 ? pa : pb));
    }
  };
  auto scales = [&]() {
    uint32_t ex[4], g, w;
    lds128(ex, S_G);
    asm volatile("ld.volatile.shared.v2.b32 {%0,%1},[%2];" : "=r"(g), "=r"(w) : "r"(S_G + 32 + (lane & 7) * 8));
    return Scales(ex[1], ex[0], ex[2], __reduce_max_sync(~0u, g) >> 23, __reduce_max_sync(~0u, w) >> 23);
  };
  pin();

  if (wg >= 2 && !assist) {
    TL(15);
    uint4 wv[8];
    #pragma unroll
    for (int i = 0; i < 8; i++) wv[i] = ldg128(wp + (8 * (i >> 1) + (i & 1)) * 256);
    pin();
    uint2 ia = {};
    uint64_t ap = gaddr(idx + cta * (kNS * kF), min(t128, kNS * kF / 2 - 1) * 8);
    asm volatile("" : "+l"(ap));
    if (tid < 384) ia = ldg64(ap);
    idle();
    uint32_t bd[8];
    #pragma unroll
    for (int i = 0; i < 8; i++) bd[i] = S_B + kc * 2048 + (cg >> 3) * 1024 + ((cg ^ i) & 7) * 16;
    uint32_t ca = S_C + v * 256 + (v < 2 ? (cg >> 2) * 64 + (lane >> 4) * 32 + (cg & 3) * 4 : xl * 8);
    uint32_t cb2 = ca + (v < 2 ? 16 : 4), od = S_RO + t128 * 8 + ((t128 * 79) >> 10) * 24, ta = v ? S_LEAD + lane * 4 : S_I + (lane & 1) * 16;
    uint32_t hm = v == 1 ? 0x7f807f80u : 0, top = pow2_bf16x2(v == 0 ? 146 : v == 1 ? 135 : 139);
    asm volatile("" : "+r"(bd[0]), "+r"(bd[1]), "+r"(bd[2]), "+r"(bd[3]), "+r"(bd[4]), "+r"(bd[5]), "+r"(bd[6]), "+r"(bd[7]),
                 "+r"(ca), "+r"(cb2), "+r"(od), "+r"(ta), "+r"(hm), "+r"(top));
    pin();
    const uint32_t y0 = (x2.x & ~hm) | (0x3f803f80u & hm), y1 = (x2.y & ~hm) | (0x3f803f80u & hm);
    const int eh = warp_amax(amax(hv)) >> 23, e = warp_amax(amax(y0, y1)) >> 23;
    TL(9);
    const uint32_t fh = pow2_bf16x2(254 - eh);
    hv.x = bmul(hv.x & 0x7f807f80u, fh); hv.y = bmul(hv.y & 0x7f807f80u, fh);
    hv.z = bmul(hv.z & 0x7f807f80u, fh); hv.w = bmul(hv.w & 0x7f807f80u, fh);
    {
      const uint32_t f = top - pow2_bf16x2(e);
      const uint32_t z0 = to_half(bmul(y0, v ? 0x3f803f80u : lane < 16 ? hv.x : hv.z), f);
      const uint32_t z1 = to_half(bmul(y1, v ? 0x3f803f80u : lane < 16 ? hv.y : hv.w), f);
      sts32_if(ta, v ? 2 : tau_of(e - 2), warp >> 1 == 6);
      sts32_if(ca, v == 3 ? x2.x : z0, tid >= 384);
      sts32(S_G + (warp ^ 12) * 4, v == 1 ? eh : e);
      sts32_if(cb2, v == 3 ? x2.y : z1, tid >= 384);
      bar_arrive_if(BAR_CONST, 384, wg == 3);
    }
    pin();
    uint32_t f0 = bmul(hv.x, pow2_bf16x2(17)), f1 = bmul(hv.y, pow2_bf16x2(17));
    uint32_t f2 = bmul(hv.z, pow2_bf16x2(17)), f3 = bmul(hv.w, pow2_bf16x2(17));
    asm volatile("" : "+r"(f0), "+r"(f1), "+r"(f2), "+r"(f3));
    pin();
    TL(13);
    uint4 cm = wv[0];
    #pragma unroll
    for (int i = 0; i < 8; i++) {
      if (i % 3 == 0) {
        asm volatile("{.reg .pred p; setp.ne.b32 p, %4, 0; @p lop3.b32 %0, %1, %2, %3, 0x96;}"
                     : "+r"(pinreg) : "r"(wv[i].x), "r"(wv[i + 1].x), "r"(i < 6 ? wv[i + 2].y : ia.x), "r"(never));
        pin();
        TL(29 + i / 3);
      }
      if (i) { cm.x = amax(cm.x, wv[i].x); cm.y = amax(cm.y, wv[i].y); cm.z = amax(cm.z, wv[i].z); cm.w = amax(cm.w, wv[i].w); }
      asm volatile("" : "+r"(cm.x), "+r"(cm.y), "+r"(cm.z), "+r"(cm.w));
      sts128(bd[i] + i * 128, to_half(wv[i].x, f0), to_half(wv[i].y, f1), to_half(wv[i].z, f2), to_half(wv[i].w, f3));
      if (i % 3 == 2) pin();
      if (i + 1 == AFM_C1) bar_arrive_if(BAR_HELP, 256, wg == 3);
    }
    const uint32_t g = warp_amax(amax(amax(bmul(cm.x, hv.x), bmul(cm.y, hv.y)), amax(bmul(cm.z, hv.z), bmul(cm.w, hv.w))));
    asm volatile("{.reg .pred p; setp.ne.b32 p, %3, 0; @p st.volatile.shared.v2.b32 [%0], {%1,%2};}"
                 :: "r"(od), "r"(row_offset(ia.x, V)), "r"(row_offset(ia.y, V)), "r"((int)(tid < 384)) : "memory");
    sts64(S_G + (warp - 4) * 8, g, warp_amax(amax(cm)));
    sts32(S_F + (warp - 8) * 4, g >= 126u << 23 || (warp == 12 && e > 137));
    TL(2);

    if (wg == 3) {
      sts32_if(pinreg, pinreg, never);
      asm volatile("setmaxnreg.dec.sync.aligned.u32 24;");
      asm volatile("fence.proxy.async.shared::cta;" ::: "memory");
      bar_arrive(BAR_START, 384);
      bar_arrive(BAR_START + 1, 384);
      return;
    }
    asm volatile("setmaxnreg.dec.sync.aligned.u32 56;");
    asm volatile("fence.proxy.async.shared::cta;" ::: "memory");
    bar_arrive(BAR_START, 384);
    bar_arrive(BAR_START + 1, 384);
    TL(12);
    rows();
    const uint32_t dst0 = S_E + (t128 >> 4) * 4 * kRowPitch + cg * 16, oa0 = S_RO + (t128 >> 4) * 16;
    uint32_t dst = dst0;
    uint32_t oa = oa0, o[4];
    auto fetch = [&](int ahead, int on) {
      #pragma unroll
      for (int mm = 0; mm < 4; mm++) {
        const int m = (mm >> 1) | (mm & 1) << 1;
        asm volatile("{.reg .pred p; setp.ne.b32 p, %2, 0; @p cp.async.cg.shared.global [%0], [%1], 16;}"
                     :: "r"(dst + ahead * kSamplePitch + m * kRowPitch), "l"(ga[m]), "r"(on & (m < 2 ? lo : hi)) : "memory");
      }
      asm volatile("cp.async.commit_group;" ::: "memory");
    };
    auto aim = [&]() {
      #pragma unroll
      for (int m = 0; m < 4; m++) ga[m] = gaddr(gsrc, o[m]);
    };
    bar_sync(BAR_B, 384);
    lds128(o, oa + 384);
    bar_sync(BAR_CONST, 256);
    fetch(2, 1);
    TL(16);
    aim();
    if (AFM_F3) bar_sync(BAR_AUX, 256);
    fetch(3, 1);
    asm volatile("cp.async.commit_group;" ::: "memory");
    if (!AFM_F3) bar_sync(BAR_AUX, 256);
    const int last = 7 - __shfl_sync(~0u, lds32(S_LEAD), 0);
    const uint32_t misfit = __ballot_sync(~0u, lds32(S_F + cg * 4));
    const int todo = 0xfc | (misfit & 0x0fff ? 1 : 0) | (misfit & 0xf0ff ? 2 : 0);
    const Scales sc = scales();
    uint32_t f, wlo, wsz, inf[4], r[4][4] = {};
    auto rescale = [&](int k, int bad) {
      bad |= sc.bad | (k > 14) | (sc.fe + 2 * k > 230);
      inf[0] = sc.tau(2 * k); inf[1] = __float_as_uint(sc.logit(2 * k)); inf[2] = __float_as_uint(sc.dot(2 * k)); inf[3] = bad;
      f = pow2_bf16x2(15 - k);
      wlo = (k + 125) << 23; wsz = bad || k < sc.kb || k < -100 ? 0 : max(sc.ka - 124, 0) << 23;
    };
    rescale(0, sc.fs < 40);
    sts128_if(S_I + lane * 16, inf[0], inf[1], inf[2], inf[3], t128 < 2);
    TL(17);
    #pragma unroll 1
    for (int n = 0; n < kNS; n++) {
      const int s = n ^ last ^ 7;
      if (!(todo >> s & 1)) continue;
      dst = dst0 + s * kSamplePitch; oa = oa0 + s * 128;
      if (__builtin_expect(s < 2, 0)) {
        bar_sync(BAR_START + s, 256);
        lds128(o, oa); aim(); fetch(0, 1);
        asm volatile("cp.async.commit_group;" ::: "memory");
      }
      lds128(o, oa + 256);
      bar_sync_if(BAR_DONE + v, 160, s == 6 + v);
      asm volatile("cp.async.wait_group 1;" ::: "memory");
      #pragma unroll
      for (int m = 0; m < 2; m++) { lds128_if(r[m], dst + m * kRowPitch, lo); lds128_if(r[m + 2], dst + (m + 2) * kRowPitch, hi); }
      uint32_t mx = 0, y[16];
      #pragma unroll
      for (int m = 0; m < 4; m++) mx = amax(mx, amax(amax(r[m][0], r[m][1]), amax(r[m][2], r[m][3])));
      mx = amax(mx, mx << 16) & 0x7fff0000u;
      int other;
      asm volatile("{.reg .pred p, q; setp.ne.b32 p, %2, 0; bar.red.or.pred q, %1, 128, p; selp.b32 %0, 1, 0, q;}"
                   : "=r"(other) : "n"(BAR_HELP), "r"((int)(lo && mx - wlo >= wsz)) : "memory");
      #pragma unroll 1
      for (;; other = 0) {
        #pragma unroll
        for (int m = 0; m < 16; m++) { y[m] = to_half(r[m >> 2][m & 3], f); asm volatile("" : "+r"(y[m])); }
        pin();
        if (__builtin_expect(!__any_sync(~0u, other), 1)) break;
        sts32(S_G + 128 + s * 16 + v * 4, __reduce_max_sync(~0u, mx));
        bar_sync(BAR_HELP, 128);
        mx = __reduce_max_sync(~0u, lds32(S_G + 128 + s * 16 + (lane & 3) * 4));
        const int k = sc.k(mx >> 23);
        rescale(k, (mx != 0) & ((k - ((int)(mx >> 23) - 131) > 7) | (sc.fs + 2 * k < 40)));
      }
      #pragma unroll
      for (int m = 0; m < 2; m++) {
        sts128_if(dst + m * kRowPitch, y[4 * m], y[4 * m + 1], y[4 * m + 2], y[4 * m + 3], lo);
        sts128_if(dst + (m + 2) * kRowPitch, y[4 * m + 8], y[4 * m + 9], y[4 * m + 10], y[4 * m + 11], hi);
      }
      sts128_if(S_I + s * 16, inf[0], inf[1], inf[2], inf[3], t128 == 127);
      bar_arrive(s < 2 ? BAR_START + s : BAR_READY + ((s - 2) & 3), 256);
      TL(16 + n);
      aim(); fetch(2, s >= 2 && s < kNS - 2);
      if (AFM_PACE && n >= 3) __nanosleep(AFM_PACE);
    }
    TL(3); TLG(0); TL(7);
    int ok;
    {
      int good = (uint32_t)__cvta_generic_to_shared(sm) == kSmemBase;
      #pragma unroll
      for (int k = 0; k < 3; k++) {
        const int q = min(t128 + 128 * k, kP - 1), i = ldg32(gaddr(ii, 4 * q)), j = ldg32(gaddr(jj, 4 * q));
        good &= (unsigned)i < (unsigned)j && (unsigned)j < (unsigned)kF && i * (2 * kF - 3 - i) + 2 * j - 2 == 2 * q;
      }
      ok = !bar_any(BAR_HELP, 128, !good);
    }
    #pragma unroll 1
    for (int s = v; s < kNS; s += 4) {
      const int smp = cta * kNS + s;
      uint2 lv = {kLeftTag ^ 0xff800000u, 0u};
      if (lane < 5) {
        const uint64_t lp = gaddr(left, (smp * 8 + lane) * 8);
        int it = 1 << 20;
        for (;;) {
          asm volatile("{.reg .b64 u; ld.relaxed.gpu.global.b64 u, [%2]; mov.b64 {%0,%1}, u;}" : "=r"(lv.x), "=r"(lv.y) : "l"(lp) : "memory");
          if (lv.x != 0 || --it == 0) break;
          __nanosleep(200);
        }
        asm volatile("st.relaxed.gpu.global.b64 [%0], %1;" :: "l"(lp), "l"(0ull) : "memory");
      }
      __syncwarp();
      if (s == last) { TL(14); }
      uint64_t op = gaddr(out, smp * 2 + (pinreg >> 5));
      const uint32_t ta = S_T + (20 * (s & 1) + 5 * (s >> 1)) * kTPitch + lane * 16;
      const int done = (BAR_DONE + s) & 15;
      bar_sync_if(s == last ? BAR_AUX : done, 160, s >= 2);
      uint32_t info[4], q[5][8];
      lds128(info, S_I + s * 16);
      #pragma unroll
      for (int j = 0; j < 4; j++) { lds128(q[j], ta + j * kTPitch); lds128(q[j] + 4, ta + j * kTPitch + 576); }
      pin();
      const float le = __uint_as_float(info[1]), ds = __uint_as_float(info[2]);
      float2 e[5], d[5];
      auto sums = [&](int j) {
        e[j] = h2f(hadd(hadd(q[j][0], q[j][2]), hadd(q[j][4], q[j][6])));
        d[j] = h2f(hadd(hadd(q[j][1], q[j][3]), hadd(q[j][5], q[j][7])));
      };
      const int plain = __any_sync(~0u, !ok || info[3] || lv.x == 0);
      const float el = __uint_as_float(lv.x ^ kLeftTag);
      float m = el;
      #pragma unroll
      for (int j = 0; j < 4; j++) {
        sums(j);
        e[j].x = __fmul_rn(e[j].x, le); e[j].y = __fmul_rn(e[j].y, le);
        m = fmaxf(m, fmaxf(e[j].x, e[j].y));
      }
      m = warp_max(m);
      float den = ex2(el - m), num = 0.f;
      const float nl = den * __uint_as_float(lv.y);
      #pragma unroll
      for (int j = 0; j < 4; j++) {
        const float x = ex2(e[j].x - m), y = ex2(e[j].y - m);
        den += x + y; num = fmaf(x, d[j].x, fmaf(y, d[j].y, num));
      }
      num = fmaf(num, ds, nl);
      asm volatile("" : "+f"(m), "+f"(den), "+f"(num), "+l"(op));
      pin();
      if (s == last) { TL(4); }
      bar_sync_if(done, 160, s == last);
      lds128(q[4], ta + 4 * kTPitch); lds128(q[4] + 4, ta + 4 * kTPitch + 576);
      if (s == last) { TL(5); }
      sums(4);
      const float u0 = fmaf(e[4].x, le, -m), u1 = fmaf(e[4].y, le, -m);
      d[4].x *= ds; d[4].y *= ds;
      const uint32_t en = __reduce_max_sync(~0u, __float_as_uint(fabsf(num) + fabsf(d[4].x) + fabsf(d[4].y)) & 0x7f800000u);
      const float up = __int_as_float(__reduce_max_sync(~0u, __float_as_int(fmaxf(fmaxf(u0, u1), 0.f))));
      const float big = __uint_as_float(en + (5u << 22));
      const float x = ex2(u0 - up), y = ex2(u1 - up), f = ex2(-up);
      const int di = __reduce_add_sync(~0u, __float_as_int(fmaf(den, f, (x + 96.f) + y))) - 32 * 0x42c00000u;
      const int ni = __reduce_add_sync(~0u, __float_as_int(fmaf(num, f, fmaf(y, d[4].y, fmaf(x, d[4].x, big))))) - 32 * __float_as_int(big);
      float rd;
      asm("rcp.approx.ftz.f32 %0, %1;" : "=f"(rd) : "f"((float)di));
      float res = (float)ni * (__uint_as_float(en) * 0.0625f) * rd;
      asm volatile("st.global.b16 [%0], %1;" :: "l"(op), "h"(__bfloat16_as_ushort(__float2bfloat16(res))) : "memory");
      pin();
      if (__builtin_expect(plain, 0)) {
        res = plain_sample(idx + smp * kF, table, V, ii, jj, W, bias, h, pv, lane);
        asm volatile("st.global.b16 [%0], %1;" :: "l"(op), "h"(__bfloat16_as_ushort(__float2bfloat16(res))) : "memory");
      }
    }
    sts32_if(pinreg, pinreg, never);
    LT(1 + v);
    TL(6); TLG(1); TLDUMP();
    return;
  }
  if (__builtin_expect(assist, 0)) {
    constexpr uint32_t kGroup = 17 * 128, S_H = S_B + 16 * kGroup;
    if (AFM_DA) { uint32_t c0, c1; asm volatile("mov.u32 %0, %clock;" : "=r"(c0) :: "memory"); do asm volatile("mov.u32 %0, %clock;" : "=r"(c1) :: "memory"); while (c1 - c0 < AFM_DA); }
    const int c = lane & 3, r8 = lane & 7;
    if (wg >= 2) {
      asm volatile("setmaxnreg.dec.sync.aligned.u32 24;");
      if (wg == 3) return;
      const int kg = t128 >> 3;
      const unsigned short pk = *reinterpret_cast<const unsigned short*>(pv + 32 * (kg >> 2) + 2 * (kg & 3) + 8 * (r8 >> 1) + (r8 & 1));
      const uint64_t a = gaddr(W, (8 * (r8 >> 1) + (r8 & 1)) * 256 + kg * 16);
      #pragma unroll
      for (int n = 0; n < 16; n++)
        asm volatile("cp.async.cg.shared.global [%0], [%1], 16;" :: "r"(S_B + n * kGroup + t128 * 16), "l"(a + (32 * (n >> 2) + 2 * (n & 3)) * 256) : "memory");
      asm volatile("st.shared.b16 [%0], %1;" :: "r"(S_B + kg * kGroup + 16 * 128 + r8 * 16), "h"(pk) : "memory");
      sts128(S_H + lane * 16, hv.x, hv.y, hv.z, hv.w);
      asm volatile("cp.async.wait_all;" ::: "memory");
      asm volatile("fence.proxy.async.shared::cta;" ::: "memory");
      bar_arrive(BAR_B, 384);
      return;
    }
    sts32_if(pinreg, pinreg, never);
    asm volatile("setmaxnreg.inc.sync.aligned.u32 232;");
    asm volatile("mov.u32 %0, %laneid;" : "=r"(pinreg) :: "memory");
    const int smp = (32 * blockIdx.x + 4 * warp + (lane >> 4)) * kNS + ((lane >> 2) & 3);
    uint32_t X[2][16], Z[2][16], cb[16];
    auto row = [&](uint32_t (&d)[16], int i) {
      const uint64_t a = gaddr(table, row_offset(i, V) + c * 16);
      #pragma unroll
      for (int q = 0; q < 4; q++)
        asm volatile("ld.global.nc.v4.b32 {%0,%1,%2,%3}, [%4];" : "=r"(d[4 * q]), "=r"(d[4 * q + 1]), "=r"(d[4 * q + 2]), "=r"(d[4 * q + 3]) : "l"(a + q * 64));
    };
    {
      const uint64_t ia = gaddr(idx, smp * kF * 4);
      const uint2 j0 = ldg64(ia), j1 = ldg64(ia + 16 * kF * 4);
      #pragma unroll
      for (int j = 0; j < 16; j++) cb[j] = ldg32(gaddr(bias, c * 4) + j * 16);
      row(X[0], j0.x); row(X[1], j1.x); row(Z[0], j0.y); row(Z[1], j1.y);
    }
    uint64_t ia = gaddr(idx, (smp * kF + 2) * 4), lp = gaddr(left, smp * 64) - 16;
    int n0 = ldg32(ia), n1 = ldg32(ia + 16 * kF * 4);
    const int turn_me = keep(BAR_TURN + (tid >> 7)), turn_ot = keep(BAR_TURN + 1 - (tid >> 7));
    float acc[68] = {}, e[4] = {}, s0 = 0.f, s1 = 0.f;
    auto hand_over = [&](int on) {
      asm volatile("{.reg .pred p; .reg .b64 u, v; setp.ne.b32 p, %5, 0; mov.b64 u, {%1,%2}; mov.b64 v, {%3,%4};\n"
                   "@p st.relaxed.gpu.global.b64 [%0], u; @p st.relaxed.gpu.global.b64 [%0+1024], v;}"
                   :: "l"(lp), "r"(__float_as_uint(e[0] * 1.4426950408889634f) ^ kLeftTag), "r"(__float_as_uint(s0)),
                      "r"(__float_as_uint(e[2] * 1.4426950408889634f) ^ kLeftTag), "r"(__float_as_uint(s1)), "r"(on) : "memory");
    };
    bar_sync(BAR_B, 384);
    bar_arrive_if(BAR_TURN, 256, wg);
    TL(4);
    #pragma unroll 1
    for (int i = 0; i <= 10; i++) {
      uint32_t A[32], H[32];
      #pragma unroll
      for (int k = 0; k < 16; k++) { A[2 * k] = bmul(X[0][k], Z[0][k]); A[2 * k + 1] = bmul(X[1][k], Z[1][k]); asm volatile("" : "+r"(A[2 * k]), "+r"(A[2 * k + 1])); }
      pin();
      hand_over(c == 0 && i >= 2);
      lp += i == 6 ? 4 * 64 - 4 * 8 : 8;
      if (i == 4) { const int v0 = ldg32(ia - 4), v1 = ldg32(ia + 16 * kF * 4 - 4); row(X[0], v0); row(X[1], v1); }
      if (i < 9) { row(Z[0], n0); row(Z[1], n1); }
      ia += i == 3 ? (4 * kF - 4) * 4 : 4;
      if (i < 8) { n0 = ldg32(ia); n1 = ldg32(ia + 16 * kF * 4); }
      bar_sync(turn_me, 256);
      pin();
      #pragma unroll
      for (int j = 0; j < 32; j++)
        asm volatile("{.reg .b32 x; cvt.rn.bf16x2.f32 x, %2, %1; fma.rn.relu.bf16x2 %0, x, %3, %4;}"
                     : "=r"(H[j]) : "f"(acc[2 * j]), "f"(acc[2 * j + 1]), "r"(0x3f803f80u), "r"(cb[j >> 1]));
      s0 = acc[64]; s1 = acc[66];
      asm volatile("" : "+f"(s0), "+f"(s1));
      pin();
      sts32_if(turn_me, turn_me, never);
      wg_fence();
      #pragma unroll
      for (int ks = 0; ks < 8; ks++) wgmma_n8(e, &H[4 * ks], uint64_t(((S_H + ks * 32) >> 4) | 1 << 16) | uint64_t(8) << 32, ks);
      wg_commit();
      if (i == 10) break;
      wg_fence();
      #pragma unroll
      for (int ks = 0; ks < 8; ks++)
        wgmma_n136(acc, &A[4 * ks], uint64_t(((S_B + ks * 2 * kGroup) >> 4) | (kGroup >> 4) << 16) | uint64_t(8) << 32, ks);
      wg_commit();
      bar_arrive(turn_ot, 256);
      asm volatile("wgmma.wait_group.sync.aligned 0;" ::: "memory");
      #pragma unroll
      for (int k = 0; k < 68; k++) asm volatile("" : "+f"(acc[k]) :: "memory");
      asm volatile("" : "+f"(e[0]), "+f"(e[1]), "+f"(e[2]), "+f"(e[3]) :: "memory");
    }
    bar_arrive_if(BAR_TURN + 1, 256, !wg);
    asm volatile("wgmma.wait_group.sync.aligned 0;" ::: "memory");
    asm volatile("" : "+f"(e[0]), "+f"(e[1]), "+f"(e[2]), "+f"(e[3]) :: "memory");
    hand_over(c == 0);
    sts32_if(pinreg, pinreg, never);
    TL(6); TLDUMP();
    return;
  }

  {
    idle();
    #pragma unroll
    for (int m = 0; m < 16; m++) { r[m >> 2][m & 3] = 0; asm volatile("" : "+r"(r[m >> 2][m & 3])); }
    pin();
    rows();
    if (AFM_G1 == 2) asm volatile("{.reg .pred p; setp.ne.b32 p, %0, 0; @p nanosleep.u32 %1;}" :: "r"(wg), "n"(AFM_D1) : "memory");
    if (AFM_G1) gather(lo, hi); else gather(t < 112, t < 96);
    pin();
    if (never) pinreg = hv.x ^ hv.y ^ hv.z ^ hv.w ^ x2.x ^ x2.y;
    TL(11);
    const uint32_t c16 = keep((t & 3) * 16), sa = keep(S_C + 768 + (t & 124) * 2);
    const uint32_t dst = keep(S_E + wg * kSamplePitch + (t & 112) * (kRowPitch / 4) + (t & 15) * 16);
    uint32_t tb = keep(S_T + wg * 20 * kTPitch + (t & 124) * 4 + (t & 1) * 8 + (t & 2) * 288), la = keep(S_LEAD + (t & 31) * 4);
    uint32_t fa = keep(S_F + (t & 8 ? 32 + wg * 16 + (t & 3) * 4 : (t & 7) * 4)), other = keep(t & 31 ? 3 : 1 - (t >> 7)), me = keep(t >> 7);
    uint32_t mx = keep(lo ? 0 : 0x3f80);
    const int mixed = !hi;
    bar_sync(BAR_CONST, 384);
    uint2 sch;
    asm volatile("ld.volatile.shared.v2.b32 {%0,%1},[%2];" : "=r"(sch.x), "=r"(sch.y) : "r"(sa));
    pin();
    if (!AFM_G1 && wg) { gather(lo, hi); TL(11); }
    pin();
    bar_arrive(BAR_B, 384);
    if (AFM_C1 < 9) bar_sync_if(BAR_HELP, 256, wg);
    uint32_t cb[16], ch[16], cp[16];
    #pragma unroll
    for (int i = 0; i < 12; i++) lds128(i < 4 ? &cb[4 * i] : i < 8 ? &ch[4 * i - 16] : &cp[4 * i - 32], S_C + i * 64 + c16);
    TL(7);
    uint32_t ad[8];
    #pragma unroll
    for (int i = 0; i < 8; i++) {
      ad[i] = S_E + wg * kSamplePitch + c16 + __byte_perm(i < 4 ? sch.x : sch.y, 0, 0x4440 + (i & 3)) * 64;
      asm volatile("" : "+r"(ad[i]));
    }
    pin();
    sts32_if(pinreg, pinreg, never);
    asm volatile("setmaxnreg.inc.sync.aligned.u32 216;");
    pinreg = keep(t >> 9);
    #pragma unroll
    for (int i = 0; i < 8; i++) ad[i] += pinreg;
    tb += pinreg; la += pinreg; fa += pinreg; other += pinreg; me += pinreg;
    uint32_t open = pinreg + 2, turn_me = me + BAR_TURN, turn_ot = BAR_TURN + 1 - me, event = me + BAR_START, tv = me + 5, sv = me + 6;
    asm volatile("" : "+r"(ad[0]), "+r"(ad[1]), "+r"(ad[2]), "+r"(ad[3]), "+r"(ad[4]), "+r"(ad[5]), "+r"(ad[6]), "+r"(ad[7]), "+r"(tb),
                 "+r"(la), "+r"(fa), "+r"(other), "+r"(me), "+r"(open), "+r"(turn_me), "+r"(turn_ot), "+r"(event), "+r"(tv), "+r"(sv));
    open = keep(open); turn_me = keep(turn_me); turn_ot = keep(turn_ot); event = keep(event);
    TL(3);
    #pragma unroll
    for (int m = 0; m < 4; m++) {
      const uint32_t f = pow2_bf16x2(15);
      if (m < 2) mx = amax(amax(mx, amax(amax(r[m][0], r[m][1]), amax(r[m][2], r[m][3]))), amax(amax(r[m + 2][0], r[m + 2][1]), amax(r[m + 2][2], r[m + 2][3])));
      if (m == 3) sts32(S_F + 32 + warp * 4, __ballot_sync(~0u, (amax(mx, mx << 16) & 0x7fff0000u) - (125u << 23) >= 5u << 23));
      sts128_if(dst + m * kRowPitch, to_half(r[m][0], f), to_half(r[m][1], f), to_half(r[m][2], f), to_half(r[m][3], f), m < 2 ? lo : hi);
      if (m == 1) mx = keep(mx);
    }
    bar_sync(event, 384);

    uint32_t acc[32], A[32], S0, S1, T0, T1;
    auto mma = [&](int q) {
      wg_fence();
      #pragma unroll
      for (int ks = 2 * q; ks < 2 * q + 2; ks++) {
        const uint64_t desc = uint64_t(((S_B + ks * 4096) >> 4) | ((1024 >> 4) << 16)) | (uint64_t((2048 >> 4) | (1 << 30)) << 32);
        if (ks == 0) wgmma_n128<false>(acc, &A[0], desc); else wgmma_n128<true>(acc, &A[4 * ks], desc);
      }
    };
    auto dots = [&](int q) {
      #pragma unroll
      for (int r = 4 * q; r < 4 * q + 4; r++) {
        S0 = r ? hfma(A[2 * r], cp[r], S0) : hmul(A[0], cp[0]);
        S1 = r ? hfma(A[2 * r + 1], cp[r], S1) : hmul(A[1], cp[0]);
      }
    };
    auto wait = [&]() {
      asm volatile("wgmma.wait_group.sync.aligned 0;" ::: "memory");
      #pragma unroll
      for (int i = 0; i < 32; i++) asm volatile("" : "+r"(acc[i]) :: "memory");
    };
    auto logits = [&](uint32_t tau) {
      #pragma unroll
      for (int j = 0; j < 16; j++) {
        const uint32_t y0 = hfma_relu(cb[j], tau, acc[2 * j]), y1 = hfma_relu(cb[j], tau, acc[2 * j + 1]);
        T0 = j ? hfma(y0, ch[j], T0) : hmul(y0, ch[0]);
        T1 = j ? hfma(y1, ch[j], T1) : hmul(y1, ch[0]);
      }
    };

    auto fold_to = [&](uint32_t& d, uint32_t a, uint32_t b) {
      asm volatile("{.reg .pred p; setp.ne.b32 p, %3, 0; @!p add.rn.f16x2 %0, %1, %2;}"
                   : "+r"(d) : "r"(__byte_perm(a, b, 0x5410)), "r"(__byte_perm(a, b, 0x7632)), "r"(never));
    };

    uint32_t R[5][16], tau;
    auto next_event = [&](int base) {
      asm volatile("{.reg .pred p; setp.ne.b32 p, %3, 0; @!p add.u32 %0, %1, %2;}" : "+r"(event) : "r"(turn_me), "r"(base - BAR_TURN), "r"(never));
    };
    uint32_t eo = 0, to = 0, io = S_I + wg * 16, sn = 0;
    int run = 0, more = 1, adv = 1, second, redo;

    auto muls = [&](int j, int q) {
      constexpr int kz[5] = {2, 3, 4, 0, 3}, kx[5] = {0, 1, 1, 1, 0}, ky[5] = {1, 2, 2, 4, 4};
      #pragma unroll
      for (int i = 4 * q; i < 4 * q + 4; i++) { A[2 * i] = hmul(R[kz[j]][i], R[kx[j]][i]); A[2 * i + 1] = hmul(R[kz[j]][i], R[ky[j]][i]); }
    };
    auto load = [&](int j, int q, int late = 0) {
      constexpr int kn[5] = {3, 4, 2, 1, 0}, kNext = AFM_EXTRA ? 0 : 2 * kSamplePitch;
      const int n = kn[j];
      if (AFM_DEFER && j == 0) { lds128_if(&R[n][4 * q], ad[n] + eo + q * 64, late ? !run : run); if (late) return; }
      else if (j < 2) lds128(&R[n][4 * q], ad[n] + eo + q * 64);
      else lds128_if(&R[n][4 * q], ad[n] + eo + kNext + q * 64, j == 2 ? more && run : more);
      if (j >= 3 && (q & 1)) lds128_if(&R[2][4 * (2 * j - 6 + q / 2)], ad[2] + eo + kNext + (2 * j - 6 + q / 2) * 64, !run);
      if (j < 3) lds128_if(&R[1][4 * q], ad[5 + j] + eo + q * 64, mixed);
    };
    auto issue = [&](int j) {
      if (j) sts64(tb + to + (j - 1) * kTPitch, tv, sv);
      if (j == 4) bar_arrive_if(BAR_AUX, 160, !more && second);
      if (j) pin();
      muls(j, 0);
      if (j == 0) {
        asm volatile("{.reg .pred p; setp.ne.b32 p, %3, 0; @p st.volatile.shared.v2.b32 [%0], {%1,%2};}"
                     :: "r"(tb + to - kTPitch), "r"(tv), "r"(sv), "r"(run) : "memory");
      }
      pin();
      mma(0);
      if (j == 0) bar_arrive_if(event, 160, AFM_EXTRA ? run == 1 || run > 1 + AFM_EXTRA : run);
      muls(j, 1); dots(0); pin();
      mma(1);
      if (j == 3 && AFM_RDY == 0) { pin(); bar_sync_if(event, 256, !run); }
      load(j, 0);
      if (j == 0) tau = lds32(io);
      muls(j, 2); load(j, 1); dots(1); load(j, 2); pin();
      mma(2);
      muls(j, 3); pin();
      if (j < 4) bar_arrive(turn_ot, 256); else bar_arrive_if(turn_ot, 256, more || !second);
      load(j, 3);
      dots(2); dots(3);
      fold_to(sv, S0, S1);
      pin();
      mma(3);
      wg_commit();
      if (AFM_DEFER && j == 0) {
        #pragma unroll
        for (int q = 0; q < 4; q++) { pin(); load(0, q, 1); }
      }
      if (j == 1) bar_sync_if(event, 256, more && adv && run);
      if (j == 2 && AFM_RDY == 1) bar_sync_if(event, 256, !run);
      if (j < 4) bar_sync(turn_me, 256); else bar_sync_if(turn_me, 256, more);
      if (j == 2 && AFM_RDY == 2) bar_sync_if(event, 256, !run);
    };
    auto finish = [&](int j) {
      pin();
      wait();
      logits(tau);
      fold_to(tv, T0, T1);
      if (j == 0) next_event(BAR_READY + (sn & 2));
      if (j == 4) next_event((BAR_DONE + sn) & 15);
    };

    #pragma unroll 1
    for (int first = 1;; first = 0) {
      uint32_t lead;
      asm volatile("atom.shared.cas.b32 %0, [%1], %2, %3;" : "=r"(lead) : "r"(la), "r"(open), "r"(me) : "memory");
      const uint32_t misfit = lds32(fa);
      #pragma unroll
      for (int q = 0; q < 4; q++) {
        #pragma unroll
        for (int i = 0; i < 3; i++) lds128(&R[i][4 * q], ad[i] + q * 64);
        if (q == 0) { TL(4); }
        if (q == AFM_UNG) {
          pin();
          second = __any_sync(~0u, lead == other);
          redo = __any_sync(~0u, first && misfit);
          pin();
        }
      }
      bar_arrive_if(BAR_AUX, 256, first && second);
      bar_arrive_if(BAR_CONST, 256, first && !second);
      bar_sync_if(turn_me, 256, second && !redo);
      if (__builtin_expect(!redo, 1)) break;
      bar_sync(event, 256);
      bar_sync(event, 256);
    }
    #pragma unroll 1
    do {
      more = run < 3 + AFM_EXTRA; adv = !AFM_EXTRA || run < 1 || run >= 1 + AFM_EXTRA;
      #pragma unroll
      for (int j = 0; j < 5; j++) {
        issue(j);
        finish(j);
      }
      if (adv) { eo += 2 * kSamplePitch; to += 5 * kTPitch; io += 32; sn += 2; }
      run++;
    } while (more);
    sts64(tb + 19 * kTPitch, tv, sv);
    bar_arrive(event, 160);
    sts32_if(pinreg, pinreg, never);
    TL(6);
    TLDUMP();
  }
}

}

extern "C" void kernel_launch(void* const* d_in, const int* in_sizes, int n_in, void* d_out, int out_size) {
  (void)n_in; (void)out_size;
  void *sched = nullptr, *left = nullptr;
  cudaGetSymbolAddress(&sched, kSched);
  cudaGetSymbolAddress(&left, gLeft);
  cudaFuncSetAttribute(afm_kernel, cudaFuncAttributeMaxDynamicSharedMemorySize, kSmemBytes);
  afm_kernel<<<kB / kNS + kAssist, 512, kSmemBytes>>>(
      (const int*)d_in[0], (const __nv_bfloat16*)d_in[4],
      Vectors{{(const __nv_bfloat16*)d_in[5], (const __nv_bfloat16*)d_in[6], (const __nv_bfloat16*)d_in[7], (const __nv_bfloat16*)sched}},
      (const __nv_bfloat16*)d_in[1], (const int*)d_in[2], (const int*)d_in[3], (__nv_bfloat16*)d_out,
      (unsigned long long*)left, in_sizes[1] / kD
      );
}
```

```cpp
#include <cuda_runtime.h>
#include <cuda_bf16.h>
#include <cuda_fp16.h>
#include <stdint.h>

#define AFM_G1 0
#define AFM_WARM 2
#define AFM_X 0
#define AFM_ARR 2
#define AFM_C1 6
#define AFM_DA 450
#define AFM_GATE 3
#define AFM_PEEL 0
#define AFM_SMALL 0
#define AFM_F3 0
#define AFM_D1 700
#define AFM_UNG 0
#define AFM_I3 0
#define AFM_SPLIT 1
#define AFM_DEFER 1
#define AFM_LATE 0
#define AFM_HG 3
#define AFM_RDY 0
#define AFM_USE 1
#define AFM_PAD 0
#define AFM_NOCHK 0
#define AFM_ND 0
#define AFM_R20 0
#define AFM_RID 1
#define AFM_POLL 100
#define AFM_PACE 0
#define AFM_EXTRA 0

namespace {

constexpr int kB = 1024, kF = 26, kP = 325, kD = 128, kNS = 8;
constexpr int kAssist = 4;
constexpr int kRowPitch = 320;
constexpr int kSamplePitch = kF * kRowPitch;
constexpr int kTPitch = 1152;
constexpr uint32_t kSmemBase = 1024;
constexpr uint32_t S_B = kSmemBase;
constexpr uint32_t S_C = S_B + 32768;
constexpr uint32_t S_G = S_C + 1024;
constexpr uint32_t S_I = S_G + 256;
constexpr uint32_t S_F = S_I + 128;
constexpr uint32_t S_RO = S_F + 128;
constexpr uint32_t S_E = S_RO + 1280;
constexpr uint32_t S_T = S_E + kNS * kSamplePitch;
constexpr uint32_t S_LEAD = S_T + 39 * kTPitch;
constexpr uint32_t S_END = S_T + 40 * kTPitch;
constexpr int kSmemBytes = S_END - kSmemBase;

__device__ const uint2 kSched[32] = {
  {0x05555028u,0x5050506eu}, {0x5a323705u,0x37373773u}, {0x64551932u,0x1919190au}, {0x4b5a2823u,0x28282819u},
  {0x695a460au,0x4646466eu}, {0x78554b41u,0x4b4b4b69u}, {0x0a144b2du,0x4b4b4b73u}, {0x7d233c0au,0x3c3c3c50u},
  {0x6e143723u,0x37373778u}, {0x73195046u,0x50505078u}, {0x2d5a500fu,0x50505041u}, {0x6e0f4b32u,0x4b4b4b3cu},
  {0x69145032u,0x5050501eu}, {0x642d0523u,0x05050569u}, {0x235f4632u,0x46464641u}, {0x1e5f192du,0x1919196eu},
  {0x2d554637u,0x4646463cu}, {0x5a555f14u,0x5f5f5f7du}, {0x69190f37u,0x0f0f0f7du}, {0x64460f28u,0x0f0f0f14u},
  {0x0514193cu,0x19191941u}, {0x1e410a37u,0x0a0a0a28u}, {0x7832282du,0x2828287du}, {0x5f0f050au,0x05050578u},
  {0x3c5a001eu,0x46002878u}, {0x5523001eu,0x7373730fu}, {0x64500037u,0x005f5a4bu}, {0x735f373cu,0x00782364u},
  {0x6e005541u,0x64697d73u}, {0x695f5028u,0x73323c00u}, {0x46051e4bu,0x0073007du}, {0x7d002d1eu,0x4b6e4164u},
};
__device__ unsigned long long gLeft[kB * 8];
constexpr uint32_t kLeftTag = 0x7fc5a5a5u;

template <bool kAccumulate>
__device__ __forceinline__ void wgmma_n128(uint32_t (&d)[32], const uint32_t* a, uint64_t desc) {
  if (kAccumulate) {
    asm volatile("wgmma.mma_async.sync.aligned.m64n128k16.f16.f16.f16 "
      "{%0, %1, %2, %3, %4, %5, %6, %7, %8, %9, %10, %11, %12, %13, %14, %15, %16, %17, %18, %19, %20, %21, %22, %23, %24, %25, %26, %27, %28, %29, %30, %31}, "
      "{%32, %33, %34, %35}, %36, 1, 1, 1, 1;"
      : "+r"(d[0]), "+r"(d[1]), "+r"(d[2]), "+r"(d[3]), "+r"(d[4]), "+r"(d[5]), "+r"(d[6]), "+r"(d[7]), "+r"(d[8]), "+r"(d[9]), "+r"(d[10]), "+r"(d[11]), "+r"(d[12]), "+r"(d[13]), "+r"(d[14]), "+r"(d[15]), "+r"(d[16]), "+r"(d[17]), "+r"(d[18]), "+r"(d[19]), "+r"(d[20]), "+r"(d[21]), "+r"(d[22]), "+r"(d[23]), "+r"(d[24]), "+r"(d[25]), "+r"(d[26]), "+r"(d[27]), "+r"(d[28]), "+r"(d[29]), "+r"(d[30]), "+r"(d[31])
      : "r"(a[0]), "r"(a[1]), "r"(a[2]), "r"(a[3]), "l"(desc));
  } else {
    asm volatile("wgmma.mma_async.sync.aligned.m64n128k16.f16.f16.f16 "
      "{%0, %1, %2, %3, %4, %5, %6, %7, %8, %9, %10, %11, %12, %13, %14, %15, %16, %17, %18, %19, %20, %21, %22, %23, %24, %25, %26, %27, %28, %29, %30, %31}, "
      "{%32, %33, %34, %35}, %36, 0, 1, 1, 1;"
      : "=r"(d[0]), "=r"(d[1]), "=r"(d[2]), "=r"(d[3]), "=r"(d[4]), "=r"(d[5]), "=r"(d[6]), "=r"(d[7]), "=r"(d[8]), "=r"(d[9]), "=r"(d[10]), "=r"(d[11]), "=r"(d[12]), "=r"(d[13]), "=r"(d[14]), "=r"(d[15]), "=r"(d[16]), "=r"(d[17]), "=r"(d[18]), "=r"(d[19]), "=r"(d[20]), "=r"(d[21]), "=r"(d[22]), "=r"(d[23]), "=r"(d[24]), "=r"(d[25]), "=r"(d[26]), "=r"(d[27]), "=r"(d[28]), "=r"(d[29]), "=r"(d[30]), "=r"(d[31])
      : "r"(a[0]), "r"(a[1]), "r"(a[2]), "r"(a[3]), "l"(desc));
  }
}

template <bool kAccumulate>
__device__ __forceinline__ void wgmma_n96_0(uint32_t (&d)[32], const uint32_t* a, uint64_t desc) {
  if (kAccumulate)
    asm volatile("wgmma.mma_async.sync.aligned.m64n96k16.f16.f16.f16 "
      "{%0, %1, %2, %3, %4, %5, %6, %7, %8, %9, %10, %11, %12, %13, %14, %15, %16, %17, %18, %19, %20, %21, %22, %23}, {%24, %25, %26, %27}, %28, 1, 1, 1, 1;"
      : "+r"(d[0]), "+r"(d[1]), "+r"(d[2]), "+r"(d[3]), "+r"(d[4]), "+r"(d[5]), "+r"(d[6]), "+r"(d[7]), "+r"(d[8]), "+r"(d[9]), "+r"(d[10]), "+r"(d[11]), "+r"(d[12]), "+r"(d[13]), "+r"(d[14]), "+r"(d[15]), "+r"(d[16]), "+r"(d[17]), "+r"(d[18]), "+r"(d[19]), "+r"(d[20]), "+r"(d[21]), "+r"(d[22]), "+r"(d[23])
      : "r"(a[0]), "r"(a[1]), "r"(a[2]), "r"(a[3]), "l"(desc));
  if (!kAccumulate)
    asm volatile("wgmma.mma_async.sync.aligned.m64n96k16.f16.f16.f16 "
      "{%0, %1, %2, %3, %4, %5, %6, %7, %8, %9, %10, %11, %12, %13, %14, %15, %16, %17, %18, %19, %20, %21, %22, %23}, {%24, %25, %26, %27}, %28, 0, 1, 1, 1;"
      : "=r"(d[0]), "=r"(d[1]), "=r"(d[2]), "=r"(d[3]), "=r"(d[4]), "=r"(d[5]), "=r"(d[6]), "=r"(d[7]), "=r"(d[8]), "=r"(d[9]), "=r"(d[10]), "=r"(d[11]), "=r"(d[12]), "=r"(d[13]), "=r"(d[14]), "=r"(d[15]), "=r"(d[16]), "=r"(d[17]), "=r"(d[18]), "=r"(d[19]), "=r"(d[20]), "=r"(d[21]), "=r"(d[22]), "=r"(d[23])
      : "r"(a[0]), "r"(a[1]), "r"(a[2]), "r"(a[3]), "l"(desc));
}
template <bool kAccumulate>
__device__ __forceinline__ void wgmma_n32_24(uint32_t (&d)[32], const uint32_t* a, uint64_t desc) {
  if (kAccumulate)
    asm volatile("wgmma.mma_async.sync.aligned.m64n32k16.f16.f16.f16 "
      "{%0, %1, %2, %3, %4, %5, %6, %7}, {%8, %9, %10, %11}, %12, 1, 1, 1, 1;"
      : "+r"(d[24]), "+r"(d[25]), "+r"(d[26]), "+r"(d[27]), "+r"(d[28]), "+r"(d[29]), "+r"(d[30]), "+r"(d[31])
      : "r"(a[0]), "r"(a[1]), "r"(a[2]), "r"(a[3]), "l"(desc));
  if (!kAccumulate)
    asm volatile("wgmma.mma_async.sync.aligned.m64n32k16.f16.f16.f16 "
      "{%0, %1, %2, %3, %4, %5, %6, %7}, {%8, %9, %10, %11}, %12, 0, 1, 1, 1;"
      : "=r"(d[24]), "=r"(d[25]), "=r"(d[26]), "=r"(d[27]), "=r"(d[28]), "=r"(d[29]), "=r"(d[30]), "=r"(d[31])
      : "r"(a[0]), "r"(a[1]), "r"(a[2]), "r"(a[3]), "l"(desc));
}
__device__ __forceinline__ void wgmma_n136(float (&d)[68], const uint32_t* a, uint64_t desc, int accumulate) {
  asm volatile("{.reg .pred p; setp.ne.b32 p, %73, 0; wgmma.mma_async.sync.aligned.m64n136k16.f32.bf16.bf16 "
    "{%0, %1, %2, %3, %4, %5, %6, %7, %8, %9, %10, %11, %12, %13, %14, %15, %16, %17, %18, %19, %20, %21, %22, %23, %24, %25, %26, %27, %28, %29, %30, %31, %32, %33, %34, %35, %36, %37, %38, %39, %40, %41, %42, %43, %44, %45, %46, %47, %48, %49, %50, %51, %52, %53, %54, %55, %56, %57, %58, %59, %60, %61, %62, %63, %64, %65, %66, %67}, "
    "{%68, %69, %70, %71}, %72, p, 1, 1, 1;}"
    : "+f"(d[0]), "+f"(d[1]), "+f"(d[2]), "+f"(d[3]), "+f"(d[4]), "+f"(d[5]), "+f"(d[6]), "+f"(d[7]), "+f"(d[8]), "+f"(d[9]), "+f"(d[10]), "+f"(d[11]), "+f"(d[12]), "+f"(d[13]), "+f"(d[14]), "+f"(d[15]), "+f"(d[16]), "+f"(d[17]), "+f"(d[18]), "+f"(d[19]), "+f"(d[20]), "+f"(d[21]), "+f"(d[22]), "+f"(d[23]), "+f"(d[24]), "+f"(d[25]), "+f"(d[26]), "+f"(d[27]), "+f"(d[28]), "+f"(d[29]), "+f"(d[30]), "+f"(d[31]), "+f"(d[32]), "+f"(d[33]), "+f"(d[34]), "+f"(d[35]), "+f"(d[36]), "+f"(d[37]), "+f"(d[38]), "+f"(d[39]), "+f"(d[40]), "+f"(d[41]), "+f"(d[42]), "+f"(d[43]), "+f"(d[44]), "+f"(d[45]), "+f"(d[46]), "+f"(d[47]), "+f"(d[48]), "+f"(d[49]), "+f"(d[50]), "+f"(d[51]), "+f"(d[52]), "+f"(d[53]), "+f"(d[54]), "+f"(d[55]), "+f"(d[56]), "+f"(d[57]), "+f"(d[58]), "+f"(d[59]), "+f"(d[60]), "+f"(d[61]), "+f"(d[62]), "+f"(d[63]), "+f"(d[64]), "+f"(d[65]), "+f"(d[66]), "+f"(d[67])
    : "r"(a[0]), "r"(a[1]), "r"(a[2]), "r"(a[3]), "l"(desc), "r"(accumulate));
}
__device__ __forceinline__ void wgmma_n8(float (&d)[4], const uint32_t* a, uint64_t desc, int accumulate) {
  asm volatile("{.reg .pred p; setp.ne.b32 p, %9, 0; wgmma.mma_async.sync.aligned.m64n8k16.f32.bf16.bf16 "
    "{%0, %1, %2, %3}, {%4, %5, %6, %7}, %8, p, 1, 1, 0;}"
    : "+f"(d[0]), "+f"(d[1]), "+f"(d[2]), "+f"(d[3])
    : "r"(a[0]), "r"(a[1]), "r"(a[2]), "r"(a[3]), "l"(desc), "r"(accumulate));
}

__device__ __forceinline__ uint32_t hmul(uint32_t a, uint32_t b) {
  uint32_t r; asm volatile("mul.rn.f16x2 %0,%1,%2;" : "=r"(r) : "r"(a), "r"(b)); return r;
}
__device__ __forceinline__ uint32_t hadd(uint32_t a, uint32_t b) {
  uint32_t r; asm volatile("add.rn.f16x2 %0,%1,%2;" : "=r"(r) : "r"(a), "r"(b)); return r;
}
__device__ __forceinline__ uint32_t hfma(uint32_t a, uint32_t b, uint32_t c) {
  uint32_t r; asm volatile("fma.rn.f16x2 %0,%1,%2,%3;" : "=r"(r) : "r"(a), "r"(b), "r"(c)); return r;
}
__device__ __forceinline__ uint32_t hfma_relu(uint32_t a, uint32_t b, uint32_t c) {
  uint32_t r; asm volatile("fma.rn.relu.f16x2 %0,%1,%2,%3;" : "=r"(r) : "r"(a), "r"(b), "r"(c)); return r;
}
__device__ __forceinline__ float2 h2f(uint32_t v) { return __half22float2(*reinterpret_cast<__half2*>(&v)); }
__device__ __forceinline__ uint32_t bmul(uint32_t a, uint32_t b) {
  uint32_t r; asm("mul.rn.bf16x2 %0,%1,%2;" : "=r"(r) : "r"(a), "r"(b)); return r;
}
__device__ __forceinline__ uint32_t amax(uint32_t a, uint32_t b) {
  uint32_t r; asm("max.NaN.xorsign.abs.bf16x2 %0,%1,%2;" : "=r"(r) : "r"(a), "r"(b)); return r;
}
__device__ __forceinline__ uint32_t amax(const uint4& v) { return amax(amax(v.x, v.y), amax(v.z, v.w)); }
__device__ __forceinline__ uint32_t warp_amax(uint32_t m) { return __reduce_max_sync(~0u, amax(m, m << 16) & 0x7fff0000u); }
__device__ __forceinline__ uint32_t pow2_bf16x2(int field) { return field * 0x00800080u; }
__device__ __forceinline__ uint32_t to_half(uint32_t x, uint32_t f) {
  const uint32_t y = bmul(x, f);
  return y + 7u * (y & 0x0fff0fffu);
}
__device__ __forceinline__ void lds128(uint32_t* r, uint32_t addr) {
  asm volatile("ld.volatile.shared.v4.b32 {%0,%1,%2,%3},[%4];"
               : "=r"(r[0]), "=r"(r[1]), "=r"(r[2]), "=r"(r[3]) : "r"(addr));
}
__device__ __forceinline__ void lds128_if(uint32_t* r, uint32_t addr, int pr) {
  asm volatile("{.reg .pred p; setp.ne.b32 p, %5, 0; @p ld.volatile.shared.v4.b32 {%0,%1,%2,%3},[%4];}"
               : "+r"(r[0]), "+r"(r[1]), "+r"(r[2]), "+r"(r[3]) : "r"(addr), "r"(pr));
}
__device__ __forceinline__ uint32_t lds32(uint32_t addr) {
  uint32_t r; asm volatile("ld.volatile.shared.b32 %0,[%1];" : "=r"(r) : "r"(addr)); return r;
}
__device__ __forceinline__ void sts32(uint32_t addr, uint32_t a) {
  asm volatile("st.volatile.shared.b32 [%0], %1;" :: "r"(addr), "r"(a) : "memory");
}
__device__ __forceinline__ void sts64(uint32_t addr, uint32_t a, uint32_t b) {
  asm volatile("st.volatile.shared.v2.b32 [%0], {%1,%2};" :: "r"(addr), "r"(a), "r"(b) : "memory");
}
__device__ __forceinline__ void sts128(uint32_t addr, uint32_t a, uint32_t b, uint32_t c, uint32_t d) {
  asm volatile("st.volatile.shared.v4.b32 [%0], {%1,%2,%3,%4};" :: "r"(addr), "r"(a), "r"(b), "r"(c), "r"(d) : "memory");
}
__device__ __forceinline__ void sts32_if(uint32_t addr, uint32_t a, int pr) {
  asm volatile("{.reg .pred p; setp.ne.b32 p, %2, 0; @p st.volatile.shared.b32 [%0], %1;}" :: "r"(addr), "r"(a), "r"(pr) : "memory");
}
__device__ __forceinline__ void sts128_if(uint32_t addr, uint32_t a, uint32_t b, uint32_t c, uint32_t d, int pr) {
  asm volatile("{.reg .pred p; setp.ne.b32 p, %5, 0; @p st.volatile.shared.v4.b32 [%0], {%1,%2,%3,%4};}"
               :: "r"(addr), "r"(a), "r"(b), "r"(c), "r"(d), "r"(pr) : "memory");
}
__device__ __forceinline__ uint64_t gaddr(uint64_t base, uint32_t off) {
  uint64_t a;
  asm("{.reg .b32 lo, hi; add.cc.u32 lo, %1, %3; addc.u32 hi, %2, 0; mov.b64 %0, {lo, hi};}"
      : "=l"(a) : "r"((uint32_t)base), "r"((uint32_t)(base >> 32)), "r"(off));
  return a;
}
__device__ __forceinline__ uint64_t gaddr(const void* base, uint32_t off) { return gaddr((uint64_t)base, off); }
__device__ __forceinline__ uint4 ldg128(uint64_t p) {
  uint4 v; asm volatile("ld.global.v4.b32 {%0,%1,%2,%3}, [%4];" : "=r"(v.x), "=r"(v.y), "=r"(v.z), "=r"(v.w) : "l"(p));
  return v;
}
__device__ __forceinline__ uint2 ldg64(uint64_t p) {
  uint2 v; asm volatile("ld.global.v2.b32 {%0,%1}, [%2];" : "=r"(v.x), "=r"(v.y) : "l"(p)); return v;
}
__device__ __forceinline__ int ldg32(uint64_t p) {
  int v; asm volatile("ld.global.b32 %0, [%1];" : "=r"(v) : "l"(p)); return v;
}
__device__ __forceinline__ uint32_t row_offset(int r, int V) { return __viaddmin_u32(r, V, r) << 8; }
__device__ __forceinline__ float ex2(float x) { float r; asm("ex2.approx.ftz.f32 %0, %1;" : "=f"(r) : "f"(x)); return r; }
__device__ __forceinline__ float warp_max(float m) {
  int i = __float_as_int(m);
  i ^= (i >> 31) & 0x7fffffff;
  i = __reduce_max_sync(~0u, i);
  i ^= (i >> 31) & 0x7fffffff;
  return __int_as_float(i);
}
__device__ __forceinline__ void bar_sync(int id, int n) { asm volatile("bar.sync %0, %1;" :: "r"(id), "r"(n) : "memory"); }
__device__ __forceinline__ void bar_arrive(int id, int n) { asm volatile("bar.arrive %0, %1;" :: "r"(id), "r"(n) : "memory"); }
__device__ __forceinline__ void bar_sync_if(int id, int n, int pr) {
  asm volatile("{.reg .pred p; setp.ne.b32 p, %2, 0; @p bar.sync %0, %1;}" :: "r"(id), "r"(n), "r"(pr) : "memory");
}
__device__ __forceinline__ void bar_arrive_if(int id, int n, int pr) {
  asm volatile("{.reg .pred p; setp.ne.b32 p, %2, 0; @p bar.arrive %0, %1;}" :: "r"(id), "r"(n), "r"(pr) : "memory");
}
__device__ __forceinline__ int bar_any(int id, int n, int pr) {
  int r;
  asm volatile("{.reg .pred p, q; setp.ne.b32 p, %3, 0; bar.red.or.pred q, %1, %2, p; selp.b32 %0, 1, 0, q;}"
               : "=r"(r) : "r"(id), "r"(n), "r"(pr) : "memory");
  return __any_sync(~0u, r);
}
__device__ __forceinline__ void wg_fence() { asm volatile("wgmma.fence.sync.aligned;" ::: "memory"); }
__device__ __forceinline__ void wg_commit() { asm volatile("wgmma.commit_group.sync.aligned;" ::: "memory"); }

__device__ __forceinline__ uint32_t tau_of(int field) {
  uint32_t r; asm("cvt.rn.f16x2.f32 %0, %1, %1;" : "=r"(r) : "f"(__int_as_float(max(field, 0) << 23))); return r;
}
struct Scales {
  int ka, kb, ft, fe, fs, bad;
  __device__ __forceinline__ Scales(int eh, int eb, int ep, int eg, int ew)
      : ka(126 + min((131 - eg) >> 1, 5)), kb((eb - 136) >> 1), ft(eb - 2), fe(eh + 5), fs(ep + 3),
        bad((eg > 133) | (eg < 114 && ew) | (ew - eg > 10) | (eb > 145) | (ep > 138) | (eh > 253)) {}
  __device__ __forceinline__ int k(int em) const { return max(em - ka, kb); }
  __device__ __forceinline__ uint32_t tau(int n) const { return tau_of(ft - n); }
  __device__ __forceinline__ float logit(int n) const { return __int_as_float(max(fe + n, 0) << 23) * 1.4426950408889634f; }
  __device__ __forceinline__ float dot(int n) const { return __int_as_float(max(fs + n, 0) << 23); }
};

#define TL(i)
#define TLB(i)
#define TLA(i)
#define TLG(i)
#define TLDUMP()

#define LT(i)
__device__ __noinline__ float plain_sample(const int* rows, const __nv_bfloat16* table, int V, const int* ii, const int* jj,
                                           const __nv_bfloat16* W, const __nv_bfloat16* bias,
                                           const __nv_bfloat16* h, const __nv_bfloat16* pv, int lane) {
  float m = -INFINITY, den = 0.f, num = 0.f;
  #pragma unroll 1
  for (int p = 0; p < kP; p++) {
    int i = ii[p], j = jj[p];
    if (i < 0) i += kF;
    if (j < 0) j += kF;
    const __nv_bfloat16* ei = table + row_offset(rows[min(max(i, 0), kF - 1)], V) / 2;
    const __nv_bfloat16* ej = table + row_offset(rows[min(max(j, 0), kF - 1)], V) / 2;
    float x[4] = {0.f, 0.f, 0.f, 0.f}, s = 0.f;
    #pragma unroll 4
    for (int d = 0; d < kD; d++) {
      const float pr = __bfloat162float(__hmul(ei[d], ej[d]));
      s = fmaf(pr, __bfloat162float(pv[d]), s);
      #pragma unroll
      for (int k = 0; k < 4; k++) x[k] = fmaf(pr, __bfloat162float(W[d * kD + lane + 32 * k]), x[k]);
    }
    float e = 0.f;
    #pragma unroll
    for (int k = 0; k < 4; k++) {
      const float y = x[k] + __bfloat162float(bias[lane + 32 * k]);
      e = fmaf(0.5f * (y + fabsf(y)), __bfloat162float(h[lane + 32 * k]), e);
    }
    #pragma unroll
    for (int o = 16; o; o >>= 1) e += __shfl_xor_sync(~0u, e, o);
    const float mn = e > m || e != e ? e : m, f = __expf(m - mn), w = __expf(e - mn);
    den = den * f + w; num = num * f + w * s; m = mn;
  }
  return num / den;
}

constexpr int BAR_CONST = 0;
constexpr int BAR_B = 1;
constexpr int BAR_START = 2;
constexpr int BAR_HELP = 4;
constexpr int BAR_AUX = 5;
constexpr int BAR_READY = 6;
constexpr int BAR_FOUR = 8;
constexpr int BAR_TURN = 10;
constexpr int BAR_DONE = 12;

struct Vectors { const __nv_bfloat16* p[4]; };

__global__ void __launch_bounds__(512, 1)
afm_kernel(const int* __restrict__ idx, const __nv_bfloat16* __restrict__ W, const __grid_constant__ Vectors vec,
           const __nv_bfloat16* __restrict__ table, const int* __restrict__ ii, const int* __restrict__ jj,
           __nv_bfloat16* __restrict__ out, unsigned long long* left, int V
           ) {
  extern __shared__ __align__(1024) uint8_t sm[];
  const int tid = threadIdx.x, lane = tid & 31, t128 = tid & 127;
  const bool assist = blockIdx.x < kAssist;
  const int cta = (blockIdx.x - kAssist) & (kB / kNS - 1);
  const __nv_bfloat16 *bias = vec.p[0], *h = vec.p[1], *pv = vec.p[2];
  const uint64_t ip = gaddr(idx + cta * (kNS * kF), (tid & 0x70) + (tid >> 7) * kF * 4);
  uint2 i0, i1;
  if (tid < 512 - 128 * AFM_I3) { i0 = ldg64(ip); i1 = ldg64(ip + 8); }
  uint32_t pinreg = lane;
  const int never = __any_sync(~0u, tid > 999);
  auto pin = [&]() {
    asm volatile("{.reg .pred p; setp.ne.b32 p, %1, 0; @p mov.u32 %0, %clock;}" : "+r"(pinreg) : "r"(never) : "memory");
  };
  auto keep = [&](uint32_t x) {
    asm volatile("{.reg .pred p; setp.ne.b32 p, %1, 0; @p mov.u32 %0, %clock;}" : "+r"(x) : "r"(never)); return x;
  };
  pin();
  const int warp = __shfl_sync(~0u, tid >> 5, 0), wg = warp >> 2, v = warp & 3;
  const int cg = lane & 15, kc = (tid >> 4) - 16, xl = 2 * cg + (lane >> 4);
  uint4 hv;
  uint2 x2;
  uint64_t hp = gaddr(h, 16 * cg);
  asm volatile("" : "+l"(hp));
  if (tid >= 256) hv = ldg128(hp);
  asm volatile("{.reg .pred p; setp.ge.u32 p, %2, 496; @p cp.async.cg.shared.global [%0], [%1], 16;}"
               :: "r"(S_T + 16 * cg), "l"(gaddr(W + cta * kD, 16 * cg)), "r"(tid) : "memory");
  pin();
  uint64_t xp = gaddr(vec.p[v], 8 * xl);
  asm volatile("" : "+l"(xp));
  if (tid >= 384) x2 = ldg64(xp);
  if (never) asm volatile("st.global.b32 [%0], 0;" :: "l"(ip) : "memory");
  pin();
  uint64_t wp = gaddr(W, (32 * (kc >> 2) + 2 * (kc & 3)) * 256 + 16 * cg);
  asm volatile("" : "+l"(wp));
  uint32_t r[4][4];
  int t, lo, hi;
  uint64_t gsrc, ga[4];
  auto idle = [&]() {
    pin();
    t = keep(tid);
    lo = (t & 127) < 112; hi = (t & 127) < 96;
    gsrc = gaddr(table, 16 * (t & 15));
    asm volatile("" : "+l"(gsrc));
  };
  auto rows = [&]() {
    ga[0] = gaddr(gsrc, row_offset(i0.x, V)); ga[1] = gaddr(gsrc, row_offset(i0.y, V));
    ga[2] = gaddr(gsrc, row_offset(i1.x, V)); ga[3] = gaddr(gsrc, row_offset(i1.y, V));
  };
  auto gather = [&](int pa, int pb) {
    #pragma unroll
    for (int mm = 0; mm < 4; mm++) {
      const int m = (mm >> 1) | (mm & 1) << 1;
      asm volatile("{.reg .pred p; setp.ne.b32 p, %5, 0; @p ld.global.nc.L1::no_allocate.v4.b32 {%0,%1,%2,%3}, [%4];}"
                   : "+r"(r[m][0]), "+r"(r[m][1]), "+r"(r[m][2]), "+r"(r[m][3]) : "l"(ga[m]), "r"(m < 2 ? pa : pb));
    }
  };
  auto warm = [&]() {
    uint32_t w0, w1;
    wg_fence();
    asm volatile("wgmma.mma_async.sync.aligned.m64n8k16.f16.f16.f16 {%0,%1}, %2, %2, 0, 1, 1, 0, 0;"
                 : "=r"(w0), "=r"(w1) : "l"(uint64_t((S_T >> 4) | (8 << 16)) | (uint64_t(16) << 32)));
    wg_commit();
    asm volatile("wgmma.wait_group.sync.aligned 0;" ::: "memory");
    asm volatile("" : "+r"(w0), "+r"(w1));
    if (never) pinreg = w0 ^ w1;
  };
  auto scales = [&]() {
    uint32_t ex[4], g, w;
    lds128(ex, S_G);
    asm volatile("ld.volatile.shared.v2.b32 {%0,%1},[%2];" : "=r"(g), "=r"(w) : "r"(S_G + 32 + (lane & 7) * 8));
    return Scales(ex[1], ex[0], ex[2], __reduce_max_sync(~0u, g) >> 23, __reduce_max_sync(~0u, w) >> 23);
  };
  pin();

  if (wg >= 2 && !assist) {
    TL(15);
    uint4 wv[8];
    #pragma unroll
    for (int i = 0; i < 8; i++) wv[i] = ldg128(wp + (8 * (i >> 1) + (i & 1)) * 256);
    pin();
    uint2 ia = {};
    uint64_t ap = gaddr(idx + cta * (kNS * kF), min(t128, kNS * kF / 2 - 1) * 8);
    asm volatile("" : "+l"(ap));
    if (tid < 384) ia = ldg64(ap);
    idle();
    uint32_t bd[8];
    #pragma unroll
    for (int i = 0; i < 8; i++) bd[i] = S_B + kc * 2048 + (cg >> 3) * 1024 + ((cg ^ i) & 7) * 16;
    uint32_t ca = S_C + v * 256 + (v < 2 ? (cg >> 2) * 64 + (lane >> 4) * 32 + (cg & 3) * 4 : xl * 8);
    uint32_t cb2 = ca + (v < 2 ? 16 : 4), od = S_RO + t128 * 8 + ((t128 * 79) >> 10) * 24, ta = v ? S_LEAD + lane * 4 : S_I + (lane & 1) * 16;
    uint32_t hm = v == 1 ? 0x7f807f80u : 0, top = pow2_bf16x2(v == 0 ? 146 : v == 1 ? 135 : 139);
    asm volatile("" : "+r"(bd[0]), "+r"(bd[1]), "+r"(bd[2]), "+r"(bd[3]), "+r"(bd[4]), "+r"(bd[5]), "+r"(bd[6]), "+r"(bd[7]),
                 "+r"(ca), "+r"(cb2), "+r"(od), "+r"(ta), "+r"(hm), "+r"(top));
    pin();
    const uint32_t y0 = (x2.x & ~hm) | (0x3f803f80u & hm), y1 = (x2.y & ~hm) | (0x3f803f80u & hm);
    const int eh = warp_amax(amax(hv)) >> 23, e = warp_amax(amax(y0, y1)) >> 23;
    TL(9);
    const uint32_t fh = pow2_bf16x2(254 - eh);
    hv.x = bmul(hv.x & 0x7f807f80u, fh); hv.y = bmul(hv.y & 0x7f807f80u, fh);
    hv.z = bmul(hv.z & 0x7f807f80u, fh); hv.w = bmul(hv.w & 0x7f807f80u, fh);
    {
      const uint32_t f = top - pow2_bf16x2(e);
      const uint32_t z0 = to_half(bmul(y0, v ? 0x3f803f80u : lane < 16 ? hv.x : hv.z), f);
      const uint32_t z1 = to_half(bmul(y1, v ? 0x3f803f80u : lane < 16 ? hv.y : hv.w), f);
      sts32_if(ta, v ? 2 : tau_of(e - 2), warp >> 1 == 6);
      sts32_if(ca, v == 3 ? x2.x : z0, tid >= 384);
      sts32(S_G + (warp ^ 12) * 4, v == 1 ? eh : e);
      sts32_if(cb2, v == 3 ? x2.y : z1, tid >= 384);
      bar_arrive_if(BAR_CONST, 384, wg == 3);
    }
    pin();
    uint32_t f0 = bmul(hv.x, pow2_bf16x2(17)), f1 = bmul(hv.y, pow2_bf16x2(17));
    uint32_t f2 = bmul(hv.z, pow2_bf16x2(17)), f3 = bmul(hv.w, pow2_bf16x2(17));
    asm volatile("" : "+r"(f0), "+r"(f1), "+r"(f2), "+r"(f3));
    pin();
    TL(13);
    uint4 cm = wv[0];
    #pragma unroll
    for (int i = 0; i < 8; i++) {
      if (i % 3 == 0) {
        asm volatile("{.reg .pred p; setp.ne.b32 p, %4, 0; @p lop3.b32 %0, %1, %2, %3, 0x96;}"
                     : "+r"(pinreg) : "r"(wv[i].x), "r"(wv[i + 1].x), "r"(i < 6 ? wv[i + 2].y : ia.x), "r"(never));
        pin();
        TL(29 + i / 3);
      }
      if (i) { cm.x = amax(cm.x, wv[i].x); cm.y = amax(cm.y, wv[i].y); cm.z = amax(cm.z, wv[i].z); cm.w = amax(cm.w, wv[i].w); }
      asm volatile("" : "+r"(cm.x), "+r"(cm.y), "+r"(cm.z), "+r"(cm.w));
      sts128(bd[i] + i * 128, to_half(wv[i].x, f0), to_half(wv[i].y, f1), to_half(wv[i].z, f2), to_half(wv[i].w, f3));
      if (i % 3 == 2) pin();
      if (i + 1 == AFM_C1) bar_arrive_if(BAR_HELP, 256, wg == 3);
    }
    const uint32_t g = warp_amax(amax(amax(bmul(cm.x, hv.x), bmul(cm.y, hv.y)), amax(bmul(cm.z, hv.z), bmul(cm.w, hv.w))));
    asm volatile("{.reg .pred p; setp.ne.b32 p, %3, 0; @p st.volatile.shared.v2.b32 [%0], {%1,%2};}"
                 :: "r"(od), "r"(row_offset(ia.x, V)), "r"(row_offset(ia.y, V)), "r"((int)(tid < 384)) : "memory");
    sts64(S_G + (warp - 4) * 8, g, warp_amax(amax(cm)));
    sts32(S_F + (warp - 8) * 4, g >= 126u << 23 || (warp == 12 && e > 137));
    TL(2);

    if (wg == 3) {
      if (AFM_WARM & 8) warm();
      sts32_if(pinreg, pinreg, never);
      asm volatile("setmaxnreg.dec.sync.aligned.u32 24;");
      asm volatile("fence.proxy.async.shared::cta;" ::: "memory");
      bar_arrive(BAR_START, 384);
      bar_arrive(BAR_START + 1, 384);
      return;
    }
    asm volatile("setmaxnreg.dec.sync.aligned.u32 56;");
    asm volatile("fence.proxy.async.shared::cta;" ::: "memory");
    bar_arrive(BAR_START, 384);
    bar_arrive(BAR_START + 1, 384);
    TL(12);
    rows();
    const uint32_t dst0 = S_E + (t128 >> 4) * 4 * kRowPitch + cg * 16, oa0 = S_RO + (t128 >> 4) * 16;
    uint32_t dst = dst0;
    uint32_t oa = oa0, o[4];
    auto fetch = [&](int ahead, int on) {
      #pragma unroll
      for (int mm = 0; mm < 4; mm++) {
        const int m = (mm >> 1) | (mm & 1) << 1;
        asm volatile("{.reg .pred p; setp.ne.b32 p, %2, 0; @p cp.async.cg.shared.global [%0], [%1], 16;}"
                     :: "r"(dst + ahead * kSamplePitch + m * kRowPitch), "l"(ga[m]), "r"(on & (m < 2 ? lo : hi)) : "memory");
      }
      asm volatile("cp.async.commit_group;" ::: "memory");
    };
    auto aim = [&]() {
      #pragma unroll
      for (int m = 0; m < 4; m++) ga[m] = gaddr(gsrc, o[m]);
    };
    bar_sync(BAR_B, 384);
    lds128(o, oa + 384);
    bar_sync(BAR_CONST, 256);
    fetch(2, 1);
    TL(16);
    aim();
    if (AFM_F3) bar_sync(BAR_AUX, 256);
    fetch(3, 1);
    asm volatile("cp.async.commit_group;" ::: "memory");
    if (!AFM_F3) bar_sync(BAR_AUX, 256);
    const int last = 7 - __shfl_sync(~0u, lds32(S_LEAD), 0);
    const uint32_t misfit = __ballot_sync(~0u, lds32(S_F + cg * 4));
    const int todo = 0xfc | (misfit & 0x0fff ? 1 : 0) | (misfit & 0xf0ff ? 2 : 0);
    const Scales sc = scales();
    uint32_t f, wlo, wsz, inf[4], r[4][4] = {}, ready_id = t;
    auto rescale = [&](int k, int bad) {
      bad |= sc.bad | (k > 14) | (sc.fe + 2 * k > 230);
      inf[0] = sc.tau(2 * k); inf[1] = __float_as_uint(sc.logit(2 * k)); inf[2] = __float_as_uint(sc.dot(2 * k)); inf[3] = bad;
      f = pow2_bf16x2(15 - k);
      wlo = (k + 125) << 23; wsz = bad || k < sc.kb || k < -100 ? 0 : max(sc.ka - 124, 0) << 23;
    };
    rescale(0, sc.fs < 40);
    sts128_if(S_I + lane * 16, inf[0], inf[1], inf[2], inf[3], t128 < 2);
    TL(17);
    #pragma unroll 1
    for (int n = todo & 3 ? 0 : 2; n < kNS; n++) {
      const int s = n ^ last ^ 7;
      if (!(todo >> s & 1)) continue;
      dst = dst0 + s * kSamplePitch; oa = oa0 + s * 128;
      if (__builtin_expect(s < 2, 0)) {
        bar_sync(BAR_START + s, 256);
        lds128(o, oa); aim(); fetch(0, 1);
        asm volatile("cp.async.commit_group;" ::: "memory");
      }
      lds128(o, oa + 256);
      bar_sync_if(BAR_DONE + v, 160, s == 6 + v);
      asm volatile("cp.async.wait_group 1;" ::: "memory");
      #pragma unroll
      for (int m = 0; m < 2; m++) { lds128_if(r[m], dst + m * kRowPitch, lo); lds128_if(r[m + 2], dst + (m + 2) * kRowPitch, hi); }
      uint32_t mx = 0, y[16];
      #pragma unroll
      for (int m = 0; m < 4; m++) mx = amax(mx, amax(amax(r[m][0], r[m][1]), amax(r[m][2], r[m][3])));
      mx = amax(mx, mx << 16) & 0x7fff0000u;
      if (AFM_RID) asm volatile("{.reg .pred p; setp.ne.b32 p, %2, 0; @!p mov.b32 %0, %1;}"
                   : "+r"(ready_id) : "r"(s < 2 ? BAR_START + s : BAR_READY + ((s - 2) & 3)), "r"(never));
      else ready_id = s < 2 ? BAR_START + s : BAR_READY + ((s - 2) & 3);
      int other;
      asm volatile("{.reg .pred p, q; setp.ne.b32 p, %2, 0; bar.red.or.pred q, %1, 128, p; selp.b32 %0, 1, 0, q;}"
                   : "=r"(other) : "n"(BAR_HELP), "r"((int)(lo && mx - wlo >= wsz)) : "memory");
      #pragma unroll 1
      for (;; other = 0) {
        #pragma unroll
        for (int m = 0; m < 16; m++) { y[m] = to_half(r[m >> 2][m & 3], f); asm volatile("" : "+r"(y[m])); }
        pin();
        if (__builtin_expect(!__any_sync(~0u, other), 1)) break;
        sts32(S_G + 128 + s * 16 + v * 4, __reduce_max_sync(~0u, mx));
        bar_sync(BAR_HELP, 128);
        mx = __reduce_max_sync(~0u, lds32(S_G + 128 + s * 16 + (lane & 3) * 4));
        const int k = sc.k(mx >> 23);
        rescale(k, (mx != 0) & ((k - ((int)(mx >> 23) - 131) > 7) | (sc.fs + 2 * k < 40)));
      }
      #pragma unroll
      for (int m = 0; m < 2; m++) {
        sts128_if(dst + m * kRowPitch, y[4 * m], y[4 * m + 1], y[4 * m + 2], y[4 * m + 3], lo);
        sts128_if(dst + (m + 2) * kRowPitch, y[4 * m + 8], y[4 * m + 9], y[4 * m + 10], y[4 * m + 11], hi);
      }
      sts128_if(S_I + s * 16, inf[0], inf[1], inf[2], inf[3], t128 == 127);
      bar_arrive(ready_id, 256);
      TL(16 + n);
      aim(); fetch(2, s >= 2 && s < kNS - 2);
      if (AFM_PACE && n >= 3) __nanosleep(AFM_PACE);
    }
    TL(3); TLG(0); TL(7);
    #pragma unroll
    for (int i = 0; i < AFM_PAD; i++) pin();
    int ok = 1;
    if (!AFM_NOCHK)
    {
      int good = (uint32_t)__cvta_generic_to_shared(sm) == kSmemBase;
      #pragma unroll
      for (int k = 0; k < 3; k++) {
        const int q = min(t128 + 128 * k, kP - 1), i = ldg32(gaddr(ii, 4 * q)), j = ldg32(gaddr(jj, 4 * q));
        good &= (unsigned)i < (unsigned)j && (unsigned)j < (unsigned)kF && i * (2 * kF - 3 - i) + 2 * j - 2 == 2 * q;
      }
      ok = !bar_any(BAR_HELP, 128, !good);
    }
    #pragma unroll 1
    for (int s = v; s < kNS; s += 4) {
      const int smp = cta * kNS + s;
      uint2 lv = {kLeftTag ^ 0xff800000u, 0u};
      if (lane < 5) {
        const uint64_t lp = gaddr(left, (smp * 8 + lane) * 8);
        int it = 1 << 20;
        for (;;) {
          asm volatile("{.reg .b64 u; ld.relaxed.gpu.global.b64 u, [%2]; mov.b64 {%0,%1}, u;}" : "=r"(lv.x), "=r"(lv.y) : "l"(lp) : "memory");
          if (lv.x != 0 || --it == 0) break;
          __nanosleep(AFM_POLL);
        }
        asm volatile("st.relaxed.gpu.global.b64 [%0], %1;" :: "l"(lp), "l"(0ull) : "memory");
      }
      __syncwarp();
      if (s >= 4) { TL(14); }
      uint64_t op = gaddr(out, smp * 2 + (pinreg >> 5));
      const uint32_t ta = S_T + (20 * (s & 1) + 5 * (s >> 1)) * kTPitch + lane * 16;
      const int done = (BAR_DONE + s) & 15;
      bar_sync_if(s >= 6 ? BAR_FOUR - 6 + s : done, 160, s >= 2);
      uint32_t info[4], q[5][8];
      lds128(info, S_I + s * 16);
      #pragma unroll
      for (int j = 0; j < 4; j++) { lds128(q[j], ta + j * kTPitch); lds128(q[j] + 4, ta + j * kTPitch + 576); }
      pin();
      const float le = __uint_as_float(info[1]), ds = __uint_as_float(info[2]);
      float2 e[5], d[5];
      auto sums = [&](int j) {
        e[j] = h2f(hadd(hadd(q[j][0], q[j][2]), hadd(q[j][4], q[j][6])));
        d[j] = h2f(hadd(hadd(q[j][1], q[j][3]), hadd(q[j][5], q[j][7])));
      };
      const int plain = __any_sync(~0u, !ok || info[3] || lv.x == 0);
      const float el = __uint_as_float(lv.x ^ kLeftTag);
      float m = el;
      #pragma unroll
      for (int j = 0; j < 4; j++) {
        sums(j);
        e[j].x = __fmul_rn(e[j].x, le); e[j].y = __fmul_rn(e[j].y, le);
        m = fmaxf(m, fmaxf(e[j].x, e[j].y));
      }
      m = warp_max(m);
      float den = ex2(el - m), num = 0.f;
      const float nl = den * __uint_as_float(lv.y);
      #pragma unroll
      for (int j = 0; j < 4; j++) {
        const float x = ex2(e[j].x - m), y = ex2(e[j].y - m);
        den += x + y; num = fmaf(x, d[j].x, fmaf(y, d[j].y, num));
      }
      num = fmaf(num, ds, nl);
      asm volatile("" : "+f"(m), "+f"(den), "+f"(num), "+l"(op));
      pin();
      if (s >= 4) { TL(4); }
      bar_sync_if(done, 160, s >= 6);
      lds128(q[4], ta + 4 * kTPitch); lds128(q[4] + 4, ta + 4 * kTPitch + 576);
      if (s >= 4) { TL(5); }
      sums(4);
      const float u0 = fmaf(e[4].x, le, -m), u1 = fmaf(e[4].y, le, -m);
      d[4].x *= ds; d[4].y *= ds;
      const uint32_t en = __reduce_max_sync(~0u, __float_as_uint(fabsf(num) + fabsf(d[4].x) + fabsf(d[4].y)) & 0x7f800000u);
      const float up = __int_as_float(__reduce_max_sync(~0u, __float_as_int(fmaxf(fmaxf(u0, u1), 0.f))));
      const float big = __uint_as_float(en + (5u << 22));
      const float x = ex2(u0 - up), y = ex2(u1 - up), f = ex2(-up);
      const int di = __reduce_add_sync(~0u, __float_as_int(fmaf(den, f, (x + 96.f) + y))) - 32 * 0x42c00000u;
      const int ni = __reduce_add_sync(~0u, __float_as_int(fmaf(num, f, fmaf(y, d[4].y, fmaf(x, d[4].x, big))))) - 32 * __float_as_int(big);
      float rd;
      asm("rcp.approx.ftz.f32 %0, %1;" : "=f"(rd) : "f"((float)di));
      float res = (float)ni * (__uint_as_float(en) * 0.0625f) * rd;
      asm volatile("st.global.b16 [%0], %1;" :: "l"(op), "h"(__bfloat16_as_ushort(__float2bfloat16(res))) : "memory");
      pin();
      if (__builtin_expect(plain, 0)) {
        res = plain_sample(idx + smp * kF, table, V, ii, jj, W, bias, h, pv, lane);
        asm volatile("st.global.b16 [%0], %1;" :: "l"(op), "h"(__bfloat16_as_ushort(__float2bfloat16(res))) : "memory");
      }
    }
    sts32_if(pinreg, pinreg, never);
    LT(1 + v);
    TL(6); TLG(1); TLDUMP();
    return;
  }
  if (__builtin_expect(assist, 0)) {
    constexpr uint32_t kBlock = 144, kGroup = 17 * kBlock, S_H = S_B + 16 * kGroup;
    if (AFM_DA) { uint32_t c0, c1; asm volatile("mov.u32 %0, %clock;" : "=r"(c0) :: "memory"); do asm volatile("mov.u32 %0, %clock;" : "=r"(c1) :: "memory"); while (c1 - c0 < AFM_DA); }
    t = keep(tid);
    if (wg >= 2) {
      const uint64_t a = gaddr(W, (64 * (wg - 2) + 8 * v + ((t >> 4) & 1)) * 256 + (t & 15) * 16);
      #pragma unroll
      for (int n = 0; n < 8; n++)
        asm volatile("cp.async.cg.shared.global [%0], [%1], 16;" :: "r"(S_B + (8 * (wg - 2) + n) * kGroup + (t & 15) * kBlock + (t & 112)),
                     "l"(a + (32 * (n >> 2) + 2 * (n & 3)) * 256) : "memory");
      pin();
      if (warp == 14) {
        #pragma unroll
        for (int k = 0; k < 4; k++)
          asm volatile("st.shared.b16 [%0], %1;" :: "r"(S_B + ((t & 12) + ((t >> 3) & 2) + (k >> 1)) * kGroup + 16 * kBlock + (2 * (t & 3) + (k & 1)) * 16),
                       "h"((unsigned short)((k < 2 ? x2.x : x2.y) >> 16 * (k & 1))) : "memory");
      }
      sts128(S_H + (t & 31) * 16, hv.x, hv.y, hv.z, hv.w);
      sts32_if(pinreg ^ i0.x ^ i0.y, i1.x ^ i1.y, never);
      asm volatile("setmaxnreg.dec.sync.aligned.u32 24;");
      asm volatile("cp.async.wait_all;" ::: "memory");
      asm volatile("fence.proxy.async.shared::cta;" ::: "memory");
      bar_arrive(BAR_B, 512);
      return;
    }
    int smp = (32 * blockIdx.x + 4 * warp + ((t >> 4) & 1)) * kNS + ((t >> 2) & 3);
    const uint2 j0 = ldg64(gaddr(idx, smp * kF * 4)), j1 = ldg64(gaddr(idx, (smp + 16) * kF * 4));
    pin();
    sts32_if(pinreg ^ i0.x ^ i0.y ^ i1.x ^ i1.y, hv.x ^ hv.y ^ hv.z ^ hv.w ^ x2.x ^ x2.y, never);
    asm volatile("setmaxnreg.inc.sync.aligned.u32 232;");
    pinreg = keep(t >> 9);
    const int c = (t & 3) + pinreg;
    smp += pinreg;
    uint32_t X[2][16], Z[2][16], cb[16];
    auto row = [&](uint32_t (&d)[16], int i) {
      const uint64_t a = gaddr(table, row_offset(i, V) + c * 16);
      #pragma unroll
      for (int q = 0; q < 4; q++)
        asm volatile("ld.global.nc.v4.b32 {%0,%1,%2,%3}, [%4];" : "=r"(d[4 * q]), "=r"(d[4 * q + 1]), "=r"(d[4 * q + 2]), "=r"(d[4 * q + 3]) : "l"(a + q * 64));
    };
    row(X[0], j0.x); row(Z[0], j0.y); row(X[1], j1.x); row(Z[1], j1.y);
    pin();
    #pragma unroll
    for (int j = 0; j < 16; j++) cb[j] = ldg32(gaddr(bias, c * 4) + j * 16);
    uint64_t ia = gaddr(idx, (smp * kF + 2) * 4), lp = gaddr(left, smp * 64) - 16;
    int n0 = ldg32(ia), n1 = ldg32(ia + 16 * kF * 4);
    const int v0 = ldg32(ia + (4 * kF - 2) * 4), v1 = ldg32(ia + (20 * kF - 2) * 4);
    float acc[68] = {}, e[4] = {}, s0 = 0.f, s1 = 0.f;
    auto hand_over = [&](int on) {
      asm volatile("{.reg .pred p; .reg .b64 u, v; setp.ne.b32 p, %5, 0; mov.b64 u, {%1,%2}; mov.b64 v, {%3,%4};\n"
                   "@p st.relaxed.gpu.global.b64 [%0], u; @p st.relaxed.gpu.global.b64 [%0+1024], v;}"
                   :: "l"(lp), "r"(__float_as_uint(e[0] * 1.4426950408889634f) ^ kLeftTag), "r"(__float_as_uint(s0)),
                      "r"(__float_as_uint(e[2] * 1.4426950408889634f) ^ kLeftTag), "r"(__float_as_uint(s1)), "r"(on) : "memory");
    };
    pin();
    bar_sync(BAR_B, 512);
    bar_arrive_if(BAR_TURN, 256, wg);
    TL(4);
    #pragma unroll 1
    for (int i = 0; i <= 10; i++) {
      uint32_t A[32], H[32];
      #pragma unroll
      for (int k = 0; k < 16; k++) { A[2 * k] = bmul(X[0][k], Z[0][k]); A[2 * k + 1] = bmul(X[1][k], Z[1][k]); asm volatile("" : "+r"(A[2 * k]), "+r"(A[2 * k + 1])); }
      pin();
      hand_over(c == 0 && i >= 2);
      lp += i == 6 ? 4 * 64 - 4 * 8 : 8;
      if (i == 4) { row(X[0], v0); row(X[1], v1); }
      if (i < 9) { row(Z[0], n0); row(Z[1], n1); }
      ia += i == 3 ? (4 * kF - 4) * 4 : 4;
      if (i < 8) { n0 = ldg32(ia); n1 = ldg32(ia + 16 * kF * 4); }
      bar_sync_if(BAR_TURN, 256, !wg);
      pin();
      bar_sync_if(BAR_TURN + 1, 256, wg);
      pin();
      #pragma unroll
      for (int j = 0; j < 32; j++)
        asm volatile("{.reg .b32 x; cvt.rn.bf16x2.f32 x, %2, %1; fma.rn.relu.bf16x2 %0, x, %3, %4;}"
                     : "=r"(H[j]) : "f"(acc[2 * j]), "f"(acc[2 * j + 1]), "r"(0x3f803f80u), "r"(cb[j >> 1]));
      s0 = acc[64]; s1 = acc[66];
      asm volatile("" : "+f"(s0), "+f"(s1));
      pin();
      sts32_if(0, 0, never);
      wg_fence();
      #pragma unroll
      for (int ks = 0; ks < 8; ks++) wgmma_n8(e, &H[4 * ks], uint64_t(((S_H + ks * 32) >> 4) | 1 << 16) | uint64_t(8) << 32, ks);
      wg_commit();
      if (i == 10) break;
      wg_fence();
      #pragma unroll
      for (int ks = 0; ks < 8; ks++)
        wgmma_n136(acc, &A[4 * ks], uint64_t(((S_B + ks * 2 * kGroup) >> 4) | (kGroup >> 4) << 16) | uint64_t(kBlock >> 4) << 32, ks);
      wg_commit();
      bar_arrive_if(BAR_TURN, 256, wg);
      pin();
      bar_arrive_if(BAR_TURN + 1, 256, !wg);
      asm volatile("wgmma.wait_group.sync.aligned 0;" ::: "memory");
      #pragma unroll
      for (int k = 0; k < 68; k++) asm volatile("" : "+f"(acc[k]) :: "memory");
      asm volatile("" : "+f"(e[0]), "+f"(e[1]), "+f"(e[2]), "+f"(e[3]) :: "memory");
    }
    bar_arrive_if(BAR_TURN + 1, 256, !wg);
    asm volatile("wgmma.wait_group.sync.aligned 0;" ::: "memory");
    asm volatile("" : "+f"(e[0]), "+f"(e[1]), "+f"(e[2]), "+f"(e[3]) :: "memory");
    hand_over(c == 0);
    sts32_if(pinreg, pinreg, never);
    TL(6); TLDUMP();
    return;
  }

  {
    idle();
    #pragma unroll
    for (int m = 0; m < 16; m++) { r[m >> 2][m & 3] = 0; asm volatile("" : "+r"(r[m >> 2][m & 3])); }
    pin();
    rows();
    if (AFM_G1 == 2 && wg) {
      uint32_t d = ga[0];
      #pragma unroll 1
      for (int i = 0; i < AFM_D1; i++) d = __shfl_xor_sync(~0u, d, 0);
      ga[0] = (ga[0] & ~0xffffffffull) | d;
    }
    if (AFM_G1) gather(lo, hi); else if (AFM_R20) gather(t < 80, t < 80); else gather(t < 112, t < 96);
    pin();
    if (never) pinreg = hv.x ^ hv.y ^ hv.z ^ hv.w ^ x2.x ^ x2.y;
    TL(11);
    const uint32_t c16 = keep((t & 3) * 16), sa = keep(S_C + 768 + (t & 124) * 2);
    const uint32_t dst = keep(S_E + wg * kSamplePitch + (t & 112) * (kRowPitch / 4) + (t & 15) * 16);
    uint32_t tb = keep(S_T + wg * 20 * kTPitch + (t & 124) * 4 + (t & 1) * 8 + (t & 2) * 288), la = keep(S_LEAD + (t & 31) * 4);
    uint32_t fa = keep(S_F + (t & 8 ? 32 + wg * 16 + (t & 3) * 4 : (t & 7) * 4)), other = keep(t & 31 ? 3 : 1 - (t >> 7)), me = keep(t >> 7);
    uint32_t mx = keep(lo && !AFM_R20 ? 0 : 0x3f80);
    const int mixed = !hi;
    if (AFM_WARM & 4) warm();
    bar_sync(BAR_CONST, 384);
    uint2 sch;
    asm volatile("ld.volatile.shared.v2.b32 {%0,%1},[%2];" : "=r"(sch.x), "=r"(sch.y) : "r"(sa));
    pin();
    if (!AFM_G1 && wg) { if (AFM_R20) gather(t < 208, (t & 127) < 80); else gather(lo, hi); TL(11); }
    pin();
    bar_arrive(BAR_B, 384);
    if (AFM_C1 < 9) bar_sync_if(BAR_HELP, 256, wg);
    uint32_t cb[16], ch[16], cp[16];
    #pragma unroll
    for (int i = 0; i < 12; i++) lds128(i < 4 ? &cb[4 * i] : i < 8 ? &ch[4 * i - 16] : &cp[4 * i - 32], S_C + i * 64 + c16);
    TL(7);
    uint32_t ad[8];
    #pragma unroll
    for (int i = 0; i < 8; i++) {
      ad[i] = S_E + wg * kSamplePitch + c16 + __byte_perm(i < 4 ? sch.x : sch.y, 0, 0x4440 + (i & 3)) * 64;
      asm volatile("" : "+r"(ad[i]));
    }
    if ((AFM_WARM & 3) == 3 || ((AFM_WARM & 3) && wg == (AFM_WARM & 3) - 1)) warm();
    pin();
    sts32_if(pinreg, pinreg, never);
    asm volatile("setmaxnreg.inc.sync.aligned.u32 216;");
    pinreg = keep(t >> 9);
    #pragma unroll
    for (int i = 0; i < 8; i++) ad[i] += pinreg;
    tb += pinreg; la += pinreg; fa += pinreg; other += pinreg; me += pinreg;
    uint32_t open = pinreg + 2, turn_me = me + BAR_TURN, turn_ot = BAR_TURN + 1 - me, event = me + BAR_START, tv = me + 5, sv = me + 6;
    asm volatile("" : "+r"(ad[0]), "+r"(ad[1]), "+r"(ad[2]), "+r"(ad[3]), "+r"(ad[4]), "+r"(ad[5]), "+r"(ad[6]), "+r"(ad[7]), "+r"(tb),
                 "+r"(la), "+r"(fa), "+r"(other), "+r"(me), "+r"(open), "+r"(turn_me), "+r"(turn_ot), "+r"(event), "+r"(tv), "+r"(sv));
    if (AFM_WARM & 16) warm();
    open = keep(open); turn_me = keep(turn_me); turn_ot = keep(turn_ot); event = keep(event);
    TL(3);
    #pragma unroll
    for (int m = 0; m < 4; m++) {
      const uint32_t f = pow2_bf16x2(15);
      if (m < 2) mx = amax(amax(mx, amax(amax(r[m][0], r[m][1]), amax(r[m][2], r[m][3]))), amax(amax(r[m + 2][0], r[m + 2][1]), amax(r[m + 2][2], r[m + 2][3])));
      if (m == 3) sts32(S_F + 32 + warp * 4, __ballot_sync(~0u, (amax(mx, mx << 16) & 0x7fff0000u) - (125u << 23) >= 5u << 23));
      sts128_if(dst + m * kRowPitch, to_half(r[m][0], f), to_half(r[m][1], f), to_half(r[m][2], f), to_half(r[m][3], f), m < 2 ? lo : hi);
      if (m == 1) mx = keep(mx);
    }
    bar_sync(event, 384);

    uint32_t acc[32], A[32], S0, S1, T0, T1;
    auto bdesc = [](int ks) {
      return uint64_t(((S_B + ks * 4096) >> 4) | ((1024 >> 4) << 16)) | (uint64_t((2048 >> 4) | (1 << 30)) << 32);
    };
    auto mma = [&](int q) {
      wg_fence();
      if (q == 0) wgmma_n128<false>(acc, &A[0], bdesc(0)); else wgmma_n128<true>(acc, &A[8 * q], bdesc(2 * q));
      wgmma_n128<true>(acc, &A[8 * q + 4], bdesc(2 * q + 1));
    };
    auto dots = [&](int q) {
      #pragma unroll
      for (int r = 4 * q; r < 4 * q + 4; r++) {
        if ((AFM_ND & 1) && r) continue;
        S0 = r ? hfma(A[2 * r], cp[r], S0) : hmul(A[0], cp[0]);
        S1 = r ? hfma(A[2 * r + 1], cp[r], S1) : hmul(A[1], cp[0]);
      }
    };
    auto wait = [&]() {
      asm volatile("wgmma.wait_group.sync.aligned 0;" ::: "memory");
      #pragma unroll
      for (int i = 0; i < 32; i++) asm volatile("" : "+r"(acc[i]) :: "memory");
    };
    auto logits = [&](uint32_t tau, int j0 = 0, int j1 = 16) {
      #pragma unroll
      for (int j = j0; j < j1; j++) {
        if ((AFM_ND & 2) && j > 7) continue;
        const uint32_t y0 = hfma_relu(cb[j], tau, acc[2 * j]), y1 = hfma_relu(cb[j], tau, acc[2 * j + 1]);
        T0 = j ? hfma(y0, ch[j], T0) : hmul(y0, ch[0]);
        T1 = j ? hfma(y1, ch[j], T1) : hmul(y1, ch[0]);
      }
    };

    auto fold_to = [&](uint32_t& d, uint32_t a, uint32_t b) {
      asm volatile("{.reg .pred p; setp.ne.b32 p, %3, 0; @!p add.rn.f16x2 %0, %1, %2;}"
                   : "+r"(d) : "r"(__byte_perm(a, b, 0x5410)), "r"(__byte_perm(a, b, 0x7632)), "r"(never));
    };

    uint32_t R[5][16], tau;
    auto next_event = [&](int base) {
      asm volatile("{.reg .pred p; setp.ne.b32 p, %3, 0; @!p add.u32 %0, %1, %2;}" : "+r"(event) : "r"(turn_me), "r"(base - BAR_TURN), "r"(never));
    };
    uint32_t eo = 0, io = S_I + wg * 16, sn = 0;
    int run = 0, more = 1, adv = 1, second, redo;

    auto muls = [&](int j, int q) {
      constexpr int kz[5] = {2, 3, 4, 0, 3}, kx[5] = {0, 1, 1, 1, 0}, ky[5] = {1, 2, 2, 4, 4};
      #pragma unroll
      for (int i = 4 * q; i < 4 * q + 4; i++) { A[2 * i] = hmul(R[kz[j]][i], R[kx[j]][i]); A[2 * i + 1] = hmul(R[kz[j]][i], R[ky[j]][i]); }
    };
    auto load = [&](int j, int q, int late = 0) {
      constexpr int kn[5] = {3, 4, 2, 1, 0}, kNext = AFM_EXTRA ? 0 : 2 * kSamplePitch;
      const int n = kn[j];
      if (AFM_DEFER && j == 0) { lds128_if(&R[n][4 * q], ad[n] + eo + q * 64, late ? !run : run); if (late) return; }
      else if (j < 2) lds128(&R[n][4 * q], ad[n] + eo + q * 64);
      else lds128_if(&R[n][4 * q], ad[n] + eo + kNext + q * 64, j == 2 ? more && run : more);
      if (j >= 3 && (q & 1)) lds128_if(&R[2][4 * (2 * j - 6 + q / 2)], ad[2] + kNext + (2 * j - 6 + q / 2) * 64, !run);
      if (j < 3) lds128_if(&R[1][4 * q], ad[5 + j] + eo + q * 64, mixed);
    };
    auto issue = [&](int j) {
      if (j) sts64(tb + (j - 1) * kTPitch, tv, sv);
      if (j == 4) bar_arrive_if(event, 160, !more);
      if (j) pin();
      muls(j, 0);
      if (j == 0) {
        asm volatile("{.reg .pred p; setp.ne.b32 p, %3, 0; @p st.volatile.shared.v2.b32 [%0], {%1,%2};}"
                     :: "r"(tb - kTPitch), "r"(tv), "r"(sv), "r"(run) : "memory");
      }
      pin();
      mma(0);
      if (j == 0 && (AFM_USE & 1)) pin();
      if (j == 0) bar_arrive_if(event, 160, AFM_EXTRA ? run == 1 || run > 1 + AFM_EXTRA : run);
      muls(j, 1); dots(0); pin();
      mma(1);
      if (j == 0 && (AFM_USE & 2)) pin();
      if (j == 3 && AFM_RDY == 0) { pin(); bar_sync_if(event, 256, !run); }
      load(j, 0);
      if (j == 0) tau = lds32(io);
      muls(j, 2); load(j, 1); dots(1); load(j, 2); pin();
      mma(2);
      muls(j, 3); pin();
      if (j < 4 || AFM_SPLIT) bar_arrive(turn_ot, 256); else bar_arrive_if(turn_ot, 256, more || !second);
      load(j, 3);
      dots(2); dots(3);
      pin();
      mma(3);
      wg_commit();
      if (AFM_DEFER && j == 0) {
        #pragma unroll
        for (int q = 0; q < 4; q++) { pin(); load(0, q, 1); }
      }
      if (j == 1) bar_sync_if(event, 256, more && adv && run);
      if (j == 2 && AFM_RDY == 1) bar_sync_if(event, 256, !run);
      if (j < 4) bar_sync(turn_me, 256); else bar_sync_if(turn_me, 256, more);
      if (j == 2 && AFM_RDY == 2) bar_sync_if(event, 256, !run);
    };
    auto finish = [&](int j) {
      pin();
      wait();
      logits(tau);
      pin();
      fold_to(sv, S0, S1);
      fold_to(tv, T0, T1);
      if (j == 0) next_event(BAR_READY + (sn & 2));
      if (j == 4) next_event((BAR_DONE + sn) & 15);
      if (j == 4) asm volatile("{.reg .pred p; setp.ne.b32 p, %2, 0; @!p add.u32 %0, %0, %1;}" : "+r"(tb) : "r"(adv * 5 * kTPitch), "r"(never));
    };

    #pragma unroll 1
    for (int first = 1;; first = 0) {
      uint32_t lead;
      asm volatile("atom.shared.cas.b32 %0, [%1], %2, %3;" : "=r"(lead) : "r"(la), "r"(open), "r"(me) : "memory");
      const uint32_t misfit = lds32(fa);
      #pragma unroll
      for (int q = 0; q < 4; q++) {
        #pragma unroll
        for (int i = 0; i < 3; i++) lds128(&R[i][4 * q], ad[i] + q * 64);
        if (q == 0) { TL(4); }
        if (q == AFM_UNG) {
          pin();
          second = __any_sync(~0u, lead == other);
          redo = __any_sync(~0u, first && misfit);
          pin();
        }
        if (q == AFM_GATE) { bar_arrive_if(BAR_AUX, 256, first && second); bar_sync_if(turn_me, 256, second && !redo); }
      }
      bar_arrive_if(BAR_CONST, 256, first && !second);
      if (__builtin_expect(!redo, 1)) break;
      bar_sync(event, 256);
      bar_sync(event, 256);
    }
    #pragma unroll 1
    do {
      more = run < 3 + AFM_EXTRA; adv = !AFM_EXTRA || run < 1 || run >= 1 + AFM_EXTRA;
      #pragma unroll
      for (int j = 0; j < 5; j++) {
        if (AFM_SPLIT && j == 4 && !more && second) goto last_tile;
        issue(j);
        finish(j);
      }
      if (adv) { eo += 2 * kSamplePitch; io += 32; sn += 2; }
      run++;
    } while (more);
    if (AFM_SPLIT && never) {
    last_tile:
      sts64(tb + 3 * kTPitch, tv, sv);
      bar_arrive(event, 160);
      pin();
      #pragma unroll
      for (int q = 0; q < 4; q++) {
        muls(4, q); pin();
        wg_fence();
        if (q == 0) wgmma_n96_0<false>(acc, &A[0], bdesc(0)); else wgmma_n96_0<true>(acc, &A[8 * q], bdesc(2 * q));
        wgmma_n96_0<true>(acc, &A[8 * q + 4], bdesc(2 * q + 1));
        dots(q); pin();
      }
      wg_commit();
      fold_to(sv, S0, S1);
      next_event((BAR_DONE + 6) & 15);
      tb += 5 * kTPitch;
      pin();
      wg_fence();
      wgmma_n32_24<false>(acc, &A[0], bdesc(0) + 68);
      #pragma unroll
      for (int ks = 1; ks < 8; ks++) wgmma_n32_24<true>(acc, &A[4 * ks], bdesc(ks) + 68);
      wg_commit();
      asm volatile("wgmma.wait_group.sync.aligned 1;" ::: "memory");
      #pragma unroll
      for (int i = 0; i < 24; i++) asm volatile("" : "+r"(acc[i]) :: "memory");
      logits(tau, 0, 12);
      pin();
      asm volatile("wgmma.wait_group.sync.aligned 0;" ::: "memory");
      #pragma unroll
      for (int i = 24; i < 32; i++) asm volatile("" : "+r"(acc[i]) :: "memory");
      logits(tau, 12, 16);
      fold_to(tv, T0, T1);
    }
    sts64(tb - kTPitch, tv, sv);
    bar_arrive(event, 160);
    sts32_if(pinreg, pinreg, never);
    TL(6);
    TLDUMP();
  }
}

}

extern "C" void kernel_launch(void* const* d_in, const int* in_sizes, int n_in, void* d_out, int out_size) {
  (void)n_in; (void)out_size;
  void *sched = nullptr, *left = nullptr;
  cudaGetSymbolAddress(&sched, kSched);
  cudaGetSymbolAddress(&left, gLeft);
  cudaFuncSetAttribute(afm_kernel, cudaFuncAttributeMaxDynamicSharedMemorySize, kSmemBytes);
  afm_kernel<<<kB / kNS + kAssist, 512, kSmemBytes>>>(
      (const int*)d_in[0], (const __nv_bfloat16*)d_in[4],
      Vectors{{(const __nv_bfloat16*)d_in[5], (const __nv_bfloat16*)d_in[6], (const __nv_bfloat16*)d_in[7], (const __nv_bfloat16*)sched}},
      (const __nv_bfloat16*)d_in[1], (const int*)d_in[2], (const int*)d_in[3], (__nv_bfloat16*)d_out,
      (unsigned long long*)left, in_sizes[1] / kD
      );
}
```
